```python
import torch

def _softmax(x, axis=-1):
    return torch.softmax(x, dim=axis)
def _gelu(x):
    return torch.nn.functional.gelu(x, approximate="tanh")
def _silu(x):
    return torch.nn.functional.silu(x)
def _sigmoid(x):
    return torch.sigmoid(x)
def _layernorm(x, axis=-1, eps=1e-5):
    m = x.mean(dim=axis, keepdim=True)
    v = x.var(dim=axis, keepdim=True, unbiased=False)
    return (x - m) / torch.sqrt(v + eps)
def _scatter_add(tgt, idx, src, axis=0):
    return tgt.clone().index_add_(axis, idx, src)
def _segment_sum(src, seg, n):
    out = torch.zeros((n,) + src.shape[1:], dtype=src.dtype)
    return out.index_add_(0, seg, src)
def _pad(x, pw):
    flat = tuple(v for pair in reversed(pw) for v in pair)
    return torch.nn.functional.pad(x, flat)

kernel_name = 'recurrent_scan__softmax_full_mha__glu_gated_reglu__prompt'

def setup_inputs():

    _w = (lambda a: (lambda t: t.to(torch.bfloat16) if t.is_floating_point() else t)(torch.as_tensor(a)))
    def _A_setup():
        B, S, D = 1, 2048, 576
        return {
            "x": _w((lambda *s: torch.randn(*s, dtype=torch.bfloat16) * 0.05)(B, S, D)),
            "wqkv": _w((lambda *s: torch.randn(*s, dtype=torch.bfloat16) * 0.2)(D, 3 * D)),
            "wo": _w((lambda *s: torch.randn(*s, dtype=torch.bfloat16) * 0.2)(D, D)),
        }
    _A_in = _A_setup()

    def _B_setup():
        B, S, D, F = 1, 2048, 576, 4608
        return {
            "x": _w((lambda *s: torch.randn(*s, dtype=torch.bfloat16) * 0.05)(B, S, D)),
            "W_gate": _w((lambda *s: torch.randn(*s, dtype=torch.bfloat16) * 0.1)(D, F) * (2.0 / D) ** 0.5),
            "W_up": _w((lambda *s: torch.randn(*s, dtype=torch.bfloat16) * 0.1)(D, F) * (2.0 / D) ** 0.5),
            "W_down": _w((lambda *s: torch.randn(*s, dtype=torch.bfloat16) * 0.1)(F, D) * (1.0 / F) ** 0.5),
        }
    _B_in = _B_setup()

    return {
        "A_x": _A_in["x"],
        "A_wqkv": _A_in["wqkv"],
        "A_wo": _A_in["wo"],
        "B_x": _B_in["x"],
        "B_W_gate": _B_in["W_gate"],
        "B_W_up": _B_in["W_up"],
        "B_W_down": _B_in["W_down"],
    }

def reference(A_x, A_wqkv, A_wo, B_x, B_W_gate, B_W_up, B_W_down):
    def _A_ref(x, wqkv, wo):
        B, S, D = x.shape
        H = 32; Dh = D // H
        qkv = (lambda x, *d: x.permute(*d))((x @ wqkv).reshape(B, S, 3, H, Dh), 2, 0, 3, 1, 4)
        q, k, v = qkv[0], qkv[1], qkv[2]
        scale = Dh ** -0.5
        scores = torch.einsum("bhqd,bhkd->bhqk", q, k) * scale
        p = _softmax(scores, axis=-1)
        o = torch.einsum("bhqk,bhkd->bhqd", p, v)
        return (lambda x, *d: x.permute(*d))(o, 0, 2, 1, 3).reshape(B, S, D) @ wo

    def _B_ref(x, W_gate, W_up, W_down):
        gate = torch.einsum("bsd,df->bsf", x, W_gate)
        up = torch.einsum("bsd,df->bsf", x, W_up)
        gate = gate * (lambda x, dt: x.to(dt))(gate > 0, gate.dtype)
        h = gate * up
        return torch.einsum("bsf,fd->bsd", h, W_down)

    x = A_x
    xn = _layernorm(x, axis=-1)
    s = _A_ref(xn, A_wqkv, A_wo)
    g = _silu(_B_ref(xn, B_W_gate, B_W_up, B_W_down))
    return x + s * g
```

```cpp
#include <cuda_runtime.h>
#include <cuda_bf16.h>
#include <cuda.h>
#include <stdint.h>

namespace {

template <uint32_t HB, int OB>
__device__ __forceinline__ void wgmma_rs_n128_tb(float (&d)[64], uint32_t a0, uint32_t a1, uint32_t a2, uint32_t a3, uint32_t lb) {
  asm volatile("{\n.reg .b32 x, y;\n.reg .b64 da, db;\n.reg .pred p;\nadd.u32 x, %68, %70;\nmov.b32 y, %69;\nmov.b64 db, {x, y};\n"
    "wgmma.mma_async.sync.aligned.m64n128k16.f32.bf16.bf16 {%0, %1, %2, %3, %4, %5, %6, %7, %8, %9, %10, %11, %12, %13, %14, %15, %16, %17, %18, %19, %20, %21, %22, %23, %24, %25, %26, %27, %28, %29, %30, %31, %32, %33, %34, %35, %36, %37, %38, %39, %40, %41, %42, %43, %44, %45, %46, %47, %48, %49, %50, %51, %52, %53, %54, %55, %56, %57, %58, %59, %60, %61, %62, %63}, {%64, %65, %66, %67}, db, 1, 1, 1, 1;\n}\n"
    : "+f"(d[0]), "+f"(d[1]), "+f"(d[2]), "+f"(d[3]), "+f"(d[4]), "+f"(d[5]), "+f"(d[6]), "+f"(d[7]), "+f"(d[8]), "+f"(d[9]), "+f"(d[10]), "+f"(d[11]), "+f"(d[12]), "+f"(d[13]), "+f"(d[14]), "+f"(d[15]), "+f"(d[16]), "+f"(d[17]), "+f"(d[18]), "+f"(d[19]), "+f"(d[20]), "+f"(d[21]), "+f"(d[22]), "+f"(d[23]), "+f"(d[24]), "+f"(d[25]), "+f"(d[26]), "+f"(d[27]), "+f"(d[28]), "+f"(d[29]), "+f"(d[30]), "+f"(d[31]), "+f"(d[32]), "+f"(d[33]), "+f"(d[34]), "+f"(d[35]), "+f"(d[36]), "+f"(d[37]), "+f"(d[38]), "+f"(d[39]), "+f"(d[40]), "+f"(d[41]), "+f"(d[42]), "+f"(d[43]), "+f"(d[44]), "+f"(d[45]), "+f"(d[46]), "+f"(d[47]), "+f"(d[48]), "+f"(d[49]), "+f"(d[50]), "+f"(d[51]), "+f"(d[52]), "+f"(d[53]), "+f"(d[54]), "+f"(d[55]), "+f"(d[56]), "+f"(d[57]), "+f"(d[58]), "+f"(d[59]), "+f"(d[60]), "+f"(d[61]), "+f"(d[62]), "+f"(d[63])
    : "r"(a0), "r"(a1), "r"(a2), "r"(a3), "r"(lb), "n"(HB), "n"(OB));
}

template <uint32_t HB, int OB>
__device__ __forceinline__ void wgmma_rs_n128_tb_p(float (&d)[64], uint32_t a0, uint32_t a1, uint32_t a2, uint32_t a3, uint32_t lb, int sd) {
  asm volatile("{\n.reg .b32 x, y;\n.reg .b64 da, db;\n.reg .pred p;\nadd.u32 x, %68, %70;\nmov.b32 y, %69;\nmov.b64 db, {x, y};\nsetp.ne.b32 p, %71, 0;\n"
    "wgmma.mma_async.sync.aligned.m64n128k16.f32.bf16.bf16 {%0, %1, %2, %3, %4, %5, %6, %7, %8, %9, %10, %11, %12, %13, %14, %15, %16, %17, %18, %19, %20, %21, %22, %23, %24, %25, %26, %27, %28, %29, %30, %31, %32, %33, %34, %35, %36, %37, %38, %39, %40, %41, %42, %43, %44, %45, %46, %47, %48, %49, %50, %51, %52, %53, %54, %55, %56, %57, %58, %59, %60, %61, %62, %63}, {%64, %65, %66, %67}, db, p, 1, 1, 1;\n}\n"
    : "+f"(d[0]), "+f"(d[1]), "+f"(d[2]), "+f"(d[3]), "+f"(d[4]), "+f"(d[5]), "+f"(d[6]), "+f"(d[7]), "+f"(d[8]), "+f"(d[9]), "+f"(d[10]), "+f"(d[11]), "+f"(d[12]), "+f"(d[13]), "+f"(d[14]), "+f"(d[15]), "+f"(d[16]), "+f"(d[17]), "+f"(d[18]), "+f"(d[19]), "+f"(d[20]), "+f"(d[21]), "+f"(d[22]), "+f"(d[23]), "+f"(d[24]), "+f"(d[25]), "+f"(d[26]), "+f"(d[27]), "+f"(d[28]), "+f"(d[29]), "+f"(d[30]), "+f"(d[31]), "+f"(d[32]), "+f"(d[33]), "+f"(d[34]), "+f"(d[35]), "+f"(d[36]), "+f"(d[37]), "+f"(d[38]), "+f"(d[39]), "+f"(d[40]), "+f"(d[41]), "+f"(d[42]), "+f"(d[43]), "+f"(d[44]), "+f"(d[45]), "+f"(d[46]), "+f"(d[47]), "+f"(d[48]), "+f"(d[49]), "+f"(d[50]), "+f"(d[51]), "+f"(d[52]), "+f"(d[53]), "+f"(d[54]), "+f"(d[55]), "+f"(d[56]), "+f"(d[57]), "+f"(d[58]), "+f"(d[59]), "+f"(d[60]), "+f"(d[61]), "+f"(d[62]), "+f"(d[63])
    : "r"(a0), "r"(a1), "r"(a2), "r"(a3), "r"(lb), "n"(HB), "n"(OB), "r"(sd));
}

template <uint32_t HA, uint32_t HB, int OA, int OB, int NA>
__device__ __forceinline__ void wgmma_ss_n128_tb(float (&d)[NA], uint32_t la, uint32_t lb) {
  asm volatile("{\n.reg .b32 x, y;\n.reg .b64 da, db;\n.reg .pred p;\nadd.u32 x, %64, %68;\nmov.b32 y, %66;\nmov.b64 da, {x, y};\nadd.u32 x, %65, %69;\nmov.b32 y, %67;\nmov.b64 db, {x, y};\n"
    "wgmma.mma_async.sync.aligned.m64n128k16.f32.bf16.bf16 {%0, %1, %2, %3, %4, %5, %6, %7, %8, %9, %10, %11, %12, %13, %14, %15, %16, %17, %18, %19, %20, %21, %22, %23, %24, %25, %26, %27, %28, %29, %30, %31, %32, %33, %34, %35, %36, %37, %38, %39, %40, %41, %42, %43, %44, %45, %46, %47, %48, %49, %50, %51, %52, %53, %54, %55, %56, %57, %58, %59, %60, %61, %62, %63}, da, db, 1, 1, 1, 0, 1;\n}\n"
    : "+f"(d[0]), "+f"(d[1]), "+f"(d[2]), "+f"(d[3]), "+f"(d[4]), "+f"(d[5]), "+f"(d[6]), "+f"(d[7]), "+f"(d[8]), "+f"(d[9]), "+f"(d[10]), "+f"(d[11]), "+f"(d[12]), "+f"(d[13]), "+f"(d[14]), "+f"(d[15]), "+f"(d[16]), "+f"(d[17]), "+f"(d[18]), "+f"(d[19]), "+f"(d[20]), "+f"(d[21]), "+f"(d[22]), "+f"(d[23]), "+f"(d[24]), "+f"(d[25]), "+f"(d[26]), "+f"(d[27]), "+f"(d[28]), "+f"(d[29]), "+f"(d[30]), "+f"(d[31]), "+f"(d[32]), "+f"(d[33]), "+f"(d[34]), "+f"(d[35]), "+f"(d[36]), "+f"(d[37]), "+f"(d[38]), "+f"(d[39]), "+f"(d[40]), "+f"(d[41]), "+f"(d[42]), "+f"(d[43]), "+f"(d[44]), "+f"(d[45]), "+f"(d[46]), "+f"(d[47]), "+f"(d[48]), "+f"(d[49]), "+f"(d[50]), "+f"(d[51]), "+f"(d[52]), "+f"(d[53]), "+f"(d[54]), "+f"(d[55]), "+f"(d[56]), "+f"(d[57]), "+f"(d[58]), "+f"(d[59]), "+f"(d[60]), "+f"(d[61]), "+f"(d[62]), "+f"(d[63])
    : "r"(la), "r"(lb), "n"(HA), "n"(HB), "n"(OA), "n"(OB));
}

template <uint32_t HA, uint32_t HB, int OA, int OB, int NA>
__device__ __forceinline__ void wgmma_ss_n128_tb_p(float (&d)[NA], uint32_t la, uint32_t lb, int sd) {
  asm volatile("{\n.reg .b32 x, y;\n.reg .b64 da, db;\n.reg .pred p;\nadd.u32 x, %64, %68;\nmov.b32 y, %66;\nmov.b64 da, {x, y};\nadd.u32 x, %65, %69;\nmov.b32 y, %67;\nmov.b64 db, {x, y};\nsetp.ne.b32 p, %70, 0;\n"
    "wgmma.mma_async.sync.aligned.m64n128k16.f32.bf16.bf16 {%0, %1, %2, %3, %4, %5, %6, %7, %8, %9, %10, %11, %12, %13, %14, %15, %16, %17, %18, %19, %20, %21, %22, %23, %24, %25, %26, %27, %28, %29, %30, %31, %32, %33, %34, %35, %36, %37, %38, %39, %40, %41, %42, %43, %44, %45, %46, %47, %48, %49, %50, %51, %52, %53, %54, %55, %56, %57, %58, %59, %60, %61, %62, %63}, da, db, p, 1, 1, 0, 1;\n}\n"
    : "+f"(d[0]), "+f"(d[1]), "+f"(d[2]), "+f"(d[3]), "+f"(d[4]), "+f"(d[5]), "+f"(d[6]), "+f"(d[7]), "+f"(d[8]), "+f"(d[9]), "+f"(d[10]), "+f"(d[11]), "+f"(d[12]), "+f"(d[13]), "+f"(d[14]), "+f"(d[15]), "+f"(d[16]), "+f"(d[17]), "+f"(d[18]), "+f"(d[19]), "+f"(d[20]), "+f"(d[21]), "+f"(d[22]), "+f"(d[23]), "+f"(d[24]), "+f"(d[25]), "+f"(d[26]), "+f"(d[27]), "+f"(d[28]), "+f"(d[29]), "+f"(d[30]), "+f"(d[31]), "+f"(d[32]), "+f"(d[33]), "+f"(d[34]), "+f"(d[35]), "+f"(d[36]), "+f"(d[37]), "+f"(d[38]), "+f"(d[39]), "+f"(d[40]), "+f"(d[41]), "+f"(d[42]), "+f"(d[43]), "+f"(d[44]), "+f"(d[45]), "+f"(d[46]), "+f"(d[47]), "+f"(d[48]), "+f"(d[49]), "+f"(d[50]), "+f"(d[51]), "+f"(d[52]), "+f"(d[53]), "+f"(d[54]), "+f"(d[55]), "+f"(d[56]), "+f"(d[57]), "+f"(d[58]), "+f"(d[59]), "+f"(d[60]), "+f"(d[61]), "+f"(d[62]), "+f"(d[63])
    : "r"(la), "r"(lb), "n"(HA), "n"(HB), "n"(OA), "n"(OB), "r"(sd));
}

template <uint32_t HA, uint32_t HB, int OA, int OB, int NA>
__device__ __forceinline__ void wgmma_ss_n64_tb(float (&d)[NA], uint32_t la, uint32_t lb) {
  asm volatile("{\n.reg .b32 x, y;\n.reg .b64 da, db;\n.reg .pred p;\nadd.u32 x, %32, %36;\nmov.b32 y, %34;\nmov.b64 da, {x, y};\nadd.u32 x, %33, %37;\nmov.b32 y, %35;\nmov.b64 db, {x, y};\n"
    "wgmma.mma_async.sync.aligned.m64n64k16.f32.bf16.bf16 {%0, %1, %2, %3, %4, %5, %6, %7, %8, %9, %10, %11, %12, %13, %14, %15, %16, %17, %18, %19, %20, %21, %22, %23, %24, %25, %26, %27, %28, %29, %30, %31}, da, db, 1, 1, 1, 0, 1;\n}\n"
    : "+f"(d[0]), "+f"(d[1]), "+f"(d[2]), "+f"(d[3]), "+f"(d[4]), "+f"(d[5]), "+f"(d[6]), "+f"(d[7]), "+f"(d[8]), "+f"(d[9]), "+f"(d[10]), "+f"(d[11]), "+f"(d[12]), "+f"(d[13]), "+f"(d[14]), "+f"(d[15]), "+f"(d[16]), "+f"(d[17]), "+f"(d[18]), "+f"(d[19]), "+f"(d[20]), "+f"(d[21]), "+f"(d[22]), "+f"(d[23]), "+f"(d[24]), "+f"(d[25]), "+f"(d[26]), "+f"(d[27]), "+f"(d[28]), "+f"(d[29]), "+f"(d[30]), "+f"(d[31])
    : "r"(la), "r"(lb), "n"(HA), "n"(HB), "n"(OA), "n"(OB));
}

template <uint32_t HA, uint32_t HB, int OA, int OB, int NA>
__device__ __forceinline__ void wgmma_ss_n64_tb_p(float (&d)[NA], uint32_t la, uint32_t lb, int sd) {
  asm volatile("{\n.reg .b32 x, y;\n.reg .b64 da, db;\n.reg .pred p;\nadd.u32 x, %32, %36;\nmov.b32 y, %34;\nmov.b64 da, {x, y};\nadd.u32 x, %33, %37;\nmov.b32 y, %35;\nmov.b64 db, {x, y};\nsetp.ne.b32 p, %38, 0;\n"
    "wgmma.mma_async.sync.aligned.m64n64k16.f32.bf16.bf16 {%0, %1, %2, %3, %4, %5, %6, %7, %8, %9, %10, %11, %12, %13, %14, %15, %16, %17, %18, %19, %20, %21, %22, %23, %24, %25, %26, %27, %28, %29, %30, %31}, da, db, p, 1, 1, 0, 1;\n}\n"
    : "+f"(d[0]), "+f"(d[1]), "+f"(d[2]), "+f"(d[3]), "+f"(d[4]), "+f"(d[5]), "+f"(d[6]), "+f"(d[7]), "+f"(d[8]), "+f"(d[9]), "+f"(d[10]), "+f"(d[11]), "+f"(d[12]), "+f"(d[13]), "+f"(d[14]), "+f"(d[15]), "+f"(d[16]), "+f"(d[17]), "+f"(d[18]), "+f"(d[19]), "+f"(d[20]), "+f"(d[21]), "+f"(d[22]), "+f"(d[23]), "+f"(d[24]), "+f"(d[25]), "+f"(d[26]), "+f"(d[27]), "+f"(d[28]), "+f"(d[29]), "+f"(d[30]), "+f"(d[31])
    : "r"(la), "r"(lb), "n"(HA), "n"(HB), "n"(OA), "n"(OB), "r"(sd));
}

template <uint32_t HA, uint32_t HB, int OA, int OB, int NA>
__device__ __forceinline__ void wgmma_ss_n72_tb(float (&d)[NA], uint32_t la, uint32_t lb) {
  asm volatile("{\n.reg .b32 x, y;\n.reg .b64 da, db;\n.reg .pred p;\nadd.u32 x, %36, %40;\nmov.b32 y, %38;\nmov.b64 da, {x, y};\nadd.u32 x, %37, %41;\nmov.b32 y, %39;\nmov.b64 db, {x, y};\n"
    "wgmma.mma_async.sync.aligned.m64n72k16.f32.bf16.bf16 {%0, %1, %2, %3, %4, %5, %6, %7, %8, %9, %10, %11, %12, %13, %14, %15, %16, %17, %18, %19, %20, %21, %22, %23, %24, %25, %26, %27, %28, %29, %30, %31, %32, %33, %34, %35}, da, db, 1, 1, 1, 0, 1;\n}\n"
    : "+f"(d[0]), "+f"(d[1]), "+f"(d[2]), "+f"(d[3]), "+f"(d[4]), "+f"(d[5]), "+f"(d[6]), "+f"(d[7]), "+f"(d[8]), "+f"(d[9]), "+f"(d[10]), "+f"(d[11]), "+f"(d[12]), "+f"(d[13]), "+f"(d[14]), "+f"(d[15]), "+f"(d[16]), "+f"(d[17]), "+f"(d[18]), "+f"(d[19]), "+f"(d[20]), "+f"(d[21]), "+f"(d[22]), "+f"(d[23]), "+f"(d[24]), "+f"(d[25]), "+f"(d[26]), "+f"(d[27]), "+f"(d[28]), "+f"(d[29]), "+f"(d[30]), "+f"(d[31]), "+f"(d[32]), "+f"(d[33]), "+f"(d[34]), "+f"(d[35])
    : "r"(la), "r"(lb), "n"(HA), "n"(HB), "n"(OA), "n"(OB));
}

template <uint32_t HB, int OB>
__device__ __forceinline__ void wgmma_rs_n32(float (&d)[16], uint32_t a0, uint32_t a1, uint32_t a2, uint32_t a3, uint32_t lb) {
  asm volatile("{\n.reg .b32 x, y;\n.reg .b64 da, db;\n.reg .pred p;\nadd.u32 x, %20, %22;\nmov.b32 y, %21;\nmov.b64 db, {x, y};\n"
    "wgmma.mma_async.sync.aligned.m64n32k16.f32.bf16.bf16 {%0, %1, %2, %3, %4, %5, %6, %7, %8, %9, %10, %11, %12, %13, %14, %15}, {%16, %17, %18, %19}, db, 1, 1, 1, 0;\n}\n"
    : "+f"(d[0]), "+f"(d[1]), "+f"(d[2]), "+f"(d[3]), "+f"(d[4]), "+f"(d[5]), "+f"(d[6]), "+f"(d[7]), "+f"(d[8]), "+f"(d[9]), "+f"(d[10]), "+f"(d[11]), "+f"(d[12]), "+f"(d[13]), "+f"(d[14]), "+f"(d[15])
    : "r"(a0), "r"(a1), "r"(a2), "r"(a3), "r"(lb), "n"(HB), "n"(OB));
}

template <uint32_t HB, int OB>
__device__ __forceinline__ void wgmma_rs_n32_z(float (&d)[16], uint32_t a0, uint32_t a1, uint32_t a2, uint32_t a3, uint32_t lb) {
  asm volatile("{\n.reg .b32 x, y;\n.reg .b64 da, db;\n.reg .pred p;\nadd.u32 x, %20, %22;\nmov.b32 y, %21;\nmov.b64 db, {x, y};\n"
    "wgmma.mma_async.sync.aligned.m64n32k16.f32.bf16.bf16 {%0, %1, %2, %3, %4, %5, %6, %7, %8, %9, %10, %11, %12, %13, %14, %15}, {%16, %17, %18, %19}, db, 0, 1, 1, 0;\n}\n"
    : "=f"(d[0]), "=f"(d[1]), "=f"(d[2]), "=f"(d[3]), "=f"(d[4]), "=f"(d[5]), "=f"(d[6]), "=f"(d[7]), "=f"(d[8]), "=f"(d[9]), "=f"(d[10]), "=f"(d[11]), "=f"(d[12]), "=f"(d[13]), "=f"(d[14]), "=f"(d[15])
    : "r"(a0), "r"(a1), "r"(a2), "r"(a3), "r"(lb), "n"(HB), "n"(OB));
}

template <uint32_t HB, int OB>
__device__ __forceinline__ void wgmma_rs_n24_tb(float (&d)[12], uint32_t a0, uint32_t a1, uint32_t a2, uint32_t a3, uint32_t lb) {
  asm volatile("{\n.reg .b32 x, y;\n.reg .b64 da, db;\n.reg .pred p;\nadd.u32 x, %16, %18;\nmov.b32 y, %17;\nmov.b64 db, {x, y};\n"
    "wgmma.mma_async.sync.aligned.m64n24k16.f32.bf16.bf16 {%0, %1, %2, %3, %4, %5, %6, %7, %8, %9, %10, %11}, {%12, %13, %14, %15}, db, 1, 1, 1, 1;\n}\n"
    : "+f"(d[0]), "+f"(d[1]), "+f"(d[2]), "+f"(d[3]), "+f"(d[4]), "+f"(d[5]), "+f"(d[6]), "+f"(d[7]), "+f"(d[8]), "+f"(d[9]), "+f"(d[10]), "+f"(d[11])
    : "r"(a0), "r"(a1), "r"(a2), "r"(a3), "r"(lb), "n"(HB), "n"(OB));
}

template <uint32_t HNS, uint32_t HK, int K0, int K1, uint32_t LIM>
__device__ __forceinline__ void att_loop(float (&o)[12], float (&sa)[16], uint32_t (&pb)[8], const uint32_t (&q)[8], uint32_t& w, uint32_t& wp,
                                           uint32_t& kb, uint32_t& kp, uint32_t& ph, uint32_t dV, uint32_t kb0, uint32_t rdelta, uint32_t two, uint32_t zero, uint32_t cnt) {
  asm volatile(
      "{\n"
      ".reg .pred pz, ptwo, pok, pm, pw;\n"
      ".reg .b32 n, t, t2, kend, pa<8>;\n"
      ".reg .f32 b<16>, e<16>, f<16>;\n"
      ".reg .b64 d0, d1, d2, d3;\n"
      "setp.ne.u32 pz, %53, 0;\n"
      "setp.ne.u32 ptwo, %52, 0;\n"
      "add.u32 kend, %50, 48;\n"
      "mov.u32 n, %54;\n"
      ".reg .f32 fz; mov.b32 fz, %53;\n"
      ".reg .f32 px, pt, pf, pp;\n"
      "shl.b32 t, %35, 16; mov.b32 f14, t; and.b32 t, %35, 0xffff0000; mov.b32 f15, t;\n"
      "add.u32 t, %36, 0; mov.b32 t2, %55; mov.b64 d0, {t, t2};\n"
      "add.u32 t, %36, 48; mov.b64 d1, {t, t2};\n"
      "add.u32 t, %36, %57; add.u32 t, t, 0; mov.b32 t2, %56; mov.b64 d2, {t, t2};\n"
      "add.u32 t, %36, %58; add.u32 t, t, 0; mov.b64 d3, {t, t2};\n"
      "LOOP:\n"
      "wgmma.wait_group.sync.aligned 0;\n"
      "ex2.approx.ftz.f32 e0, %12;\n"
      "ex2.approx.ftz.f32 e1, %13;\n"
      "cvt.rn.bf16x2.f32 %35, f15, f14;\n"
      "wgmma.fence.sync.aligned;\n"
      "wgmma.mma_async.sync.aligned.m64n24k16.f32.bf16.bf16 {%0, %1, %2, %3, %4, %5, %6, %7, %8, %9, %10, %11}, {%28, %29, %30, %31}, d0, 1, 1, 1, 1;\n"
      "wgmma.mma_async.sync.aligned.m64n24k16.f32.bf16.bf16 {%0, %1, %2, %3, %4, %5, %6, %7, %8, %9, %10, %11}, {%32, %33, %34, %35}, d1, 1, 1, 1, 1;\n"
      "wgmma.mma_async.sync.aligned.m64n32k16.f32.bf16.bf16 {b0, b1, b2, b3, b4, b5, b6, b7, b8, b9, b10, b11, b12, b13, b14, b15}, {%41, %42, %43, %44}, d2, 0, 1, 1, 0;\n"
      "wgmma.mma_async.sync.aligned.m64n32k16.f32.bf16.bf16 {b0, b1, b2, b3, b4, b5, b6, b7, b8, b9, b10, b11, b12, b13, b14, b15}, {%45, %46, %47, %48}, d3, 1, 1, 1, 0;\n"
      "wgmma.commit_group.sync.aligned;\n"
      "@pz bra.uni COLD1;\n"
      "BACK1:\n"
      "add.u32 t, %39, %51;\n"
      "@ptwo mbarrier.arrive.shared::cluster.b64 _, [t + 8];\n"
      "add.u32 t, %36, 192; mov.b32 t2, %55; mov.b64 d0, {t, t2};\n"
      "add.u32 t, %36, 240; mov.b64 d1, {t, t2};\n"
      "add.u32 t, %36, %57; add.u32 t, t, 192; mov.b32 t2, %56; mov.b64 d2, {t, t2};\n"
      "add.u32 t, %36, %58; add.u32 t, t, 192; mov.b64 d3, {t, t2};\n"
      "cvt.rn.bf16x2.f32 pa0, e1, e0;\n"
      "ex2.approx.ftz.f32 e2, %14;\n"
      "ex2.approx.ftz.f32 e3, %15;\n"
      "cvt.rn.bf16x2.f32 pa1, e3, e2;\n"
      "ex2.approx.ftz.f32 e4, %16;\n"
      "ex2.approx.ftz.f32 e5, %17;\n"
      "cvt.rn.bf16x2.f32 pa2, e5, e4;\n"
      "ex2.approx.ftz.f32 e6, %18;\n"
      "ex2.approx.ftz.f32 e7, %19;\n"
      "cvt.rn.bf16x2.f32 pa3, e7, e6;\n"
      "ex2.approx.ftz.f32 e8, %20;\n"
      "ex2.approx.ftz.f32 e9, %21;\n"
      "cvt.rn.bf16x2.f32 pa4, e9, e8;\n"
      "ex2.approx.ftz.f32 e10, %22;\n"
      "ex2.approx.ftz.f32 e11, %23;\n"
      "cvt.rn.bf16x2.f32 pa5, e11, e10;\n"
      "ex2.approx.ftz.f32 e12, %24;\n"
      "ex2.approx.ftz.f32 e13, %25;\n"
      "cvt.rn.bf16x2.f32 pa6, e13, e12;\n"
      "ex2.approx.ftz.f32 e14, %26;\n"
      "ex2.approx.ftz.f32 e15, %27;\n"
      "@pz bra.uni COLD2;\n"
      "BACK2:\n"
      "wgmma.wait_group.sync.aligned 0;\n"
      "ex2.approx.ftz.f32 f0, b0;\n"
      "ex2.approx.ftz.f32 f1, b1;\n"
      "cvt.rn.bf16x2.f32 pa7, e15, e14;\n"
      "wgmma.fence.sync.aligned;\n"
      "wgmma.mma_async.sync.aligned.m64n24k16.f32.bf16.bf16 {%0, %1, %2, %3, %4, %5, %6, %7, %8, %9, %10, %11}, {pa0, pa1, pa2, pa3}, d0, 1, 1, 1, 1;\n"
      "wgmma.mma_async.sync.aligned.m64n24k16.f32.bf16.bf16 {%0, %1, %2, %3, %4, %5, %6, %7, %8, %9, %10, %11}, {pa4, pa5, pa6, pa7}, d1, 1, 1, 1, 1;\n"
      "wgmma.mma_async.sync.aligned.m64n32k16.f32.bf16.bf16 {%12, %13, %14, %15, %16, %17, %18, %19, %20, %21, %22, %23, %24, %25, %26, %27}, {%41, %42, %43, %44}, d2, 0, 1, 1, 0;\n"
      "wgmma.mma_async.sync.aligned.m64n32k16.f32.bf16.bf16 {%12, %13, %14, %15, %16, %17, %18, %19, %20, %21, %22, %23, %24, %25, %26, %27}, {%45, %46, %47, %48}, d3, 1, 1, 1, 0;\n"
      "wgmma.commit_group.sync.aligned;\n"
      "@pz bra.uni COLD3;\n"
      "BACK3:\n"
      "mov.u32 %37, %36; mov.u32 %39, %38;\n"
      "add.u32 %36, %36, 384; add.u32 %38, %38, 16;\n"
      "setp.eq.u32 pw, %38, kend;\n"
      "selp.u32 %36, %49, %36, pw; selp.u32 %38, %50, %38, pw; selp.u32 t, 1, 0, pw; xor.b32 %40, %40, t;\n"
      "mbarrier.test_wait.parity.shared::cta.b64 pok, [%38], %40;\n"
      "add.u32 t, %36, 0; mov.b32 t2, %55; mov.b64 d0, {t, t2};\n"
      "add.u32 t, %36, 48; mov.b64 d1, {t, t2};\n"
      "add.u32 t, %36, %57; add.u32 t, t, 0; mov.b32 t2, %56; mov.b64 d2, {t, t2};\n"
      "add.u32 t, %36, %58; add.u32 t, t, 0; mov.b64 d3, {t, t2};\n"
      "sub.u32 n, n, 1; setp.ne.u32 pm, n, 0;\n"
      "cvt.rn.bf16x2.f32 %28, f1, f0;\n"
      "ex2.approx.ftz.f32 f2, b2;\n"
      "ex2.approx.ftz.f32 f3, b3;\n"
      "cvt.rn.bf16x2.f32 %29, f3, f2;\n"
      "ex2.approx.ftz.f32 f4, b4;\n"
      "ex2.approx.ftz.f32 f5, b5;\n"
      "cvt.rn.bf16x2.f32 %30, f5, f4;\n"
      "ex2.approx.ftz.f32 f6, b6;\n"
      "ex2.approx.ftz.f32 f7, b7;\n"
      "cvt.rn.bf16x2.f32 %31, f7, f6;\n"
      "ex2.approx.ftz.f32 f8, b8;\n"
      "ex2.approx.ftz.f32 f9, b9;\n"
      "cvt.rn.bf16x2.f32 %32, f9, f8;\n"
      "ex2.approx.ftz.f32 f10, b10;\n"
      "ex2.approx.ftz.f32 f11, b11;\n"
      "cvt.rn.bf16x2.f32 %33, f11, f10;\n"
      "ex2.approx.ftz.f32 f12, b12;\n"
      "ex2.approx.ftz.f32 f13, b13;\n"
      "cvt.rn.bf16x2.f32 %34, f13, f12;\n"
      "ex2.approx.ftz.f32 f14, b14;\n"
      "ex2.approx.ftz.f32 f15, b15;\n"
      "and.pred pw, pok, pm;\n"
      "@pw bra.uni LOOP;\n"
      "@pok bra.uni END;\n"
      "mov.u32 t, 0;\n"
      "WAIT:\n"
      "mbarrier.try_wait.parity.shared::cta.b64 pok, [%38], %40;\n"
      "@pok bra.uni WDONE;\n"
      "add.u32 t, t, 1; setp.gt.u32 pw, t, %59; @pw trap;\n"
      "bra.uni WAIT;\n"
      "WDONE:\n"
      "@pm bra.uni LOOP;\n"
      "bra.uni END;\n"
      "COLD1:\n"
      "mov.u32 t, %53;\n"
      "COLD1L:\n"
      "add.f32 %14, %14, %14; add.f32 %15, %15, %15; add.f32 %16, %16, %16; add.f32 %17, %17, %17; add.f32 %18, %18, %18; add.f32 %19, %19, %19; add.f32 %20, %20, %20; add.f32 %21, %21, %21; add.f32 %22, %22, %22; add.f32 %23, %23, %23; add.f32 %24, %24, %24; add.f32 %25, %25, %25; add.f32 %26, %26, %26; add.f32 %27, %27, %27;\n"
      "sub.u32 t, t, 1; setp.ne.u32 pw, t, 0; @pw bra.uni COLD1L;\n"
      "bra.uni BACK1;\n"
      "COLD2:\n"
      "mov.u32 t, %53;\n"
      "COLD2L:\n"
      "add.f32 e14, e14, e14; add.f32 e15, e15, e15;\n"
      "sub.u32 t, t, 1; setp.ne.u32 pw, t, 0; @pw bra.uni COLD2L;\n"
      "bra.uni BACK2;\n"
      "COLD3:\n"
      "mov.u32 t, %53;\n"
      "COLD3L:\n"
      "add.f32 b2, b2, b2; add.f32 b3, b3, b3; add.f32 b4, b4, b4; add.f32 b5, b5, b5; add.f32 b6, b6, b6; add.f32 b7, b7, b7; add.f32 b8, b8, b8; add.f32 b9, b9, b9; add.f32 b10, b10, b10; add.f32 b11, b11, b11; add.f32 b12, b12, b12; add.f32 b13, b13, b13; add.f32 b14, b14, b14; add.f32 b15, b15, b15;\n"
      "sub.u32 t, t, 1; setp.ne.u32 pw, t, 0; @pw bra.uni COLD3L;\n"
      "bra.uni BACK3;\n"
      "END:\n"
      "cvt.rn.bf16x2.f32 %35, f15, f14;\n"
      "}\n"
      : "+f"(o[0]), "+f"(o[1]), "+f"(o[2]), "+f"(o[3]), "+f"(o[4]), "+f"(o[5]), "+f"(o[6]), "+f"(o[7]), "+f"(o[8]), "+f"(o[9]), "+f"(o[10]), "+f"(o[11]), "+f"(sa[0]), "+f"(sa[1]), "+f"(sa[2]), "+f"(sa[3]), "+f"(sa[4]), "+f"(sa[5]), "+f"(sa[6]), "+f"(sa[7]), "+f"(sa[8]), "+f"(sa[9]), "+f"(sa[10]), "+f"(sa[11]), "+f"(sa[12]), "+f"(sa[13]), "+f"(sa[14]), "+f"(sa[15]), "+r"(pb[0]), "+r"(pb[1]), "+r"(pb[2]), "+r"(pb[3]), "+r"(pb[4]), "+r"(pb[5]), "+r"(pb[6]), "+r"(pb[7]), "+r"(w), "+r"(wp), "+r"(kb), "+r"(kp), "+r"(ph)
      : "r"(q[0]), "r"(q[1]), "r"(q[2]), "r"(q[3]), "r"(q[4]), "r"(q[5]), "r"(q[6]), "r"(q[7]), "r"(dV), "r"(kb0), "r"(rdelta), "r"(two), "r"(zero), "r"(cnt), "n"(HNS), "n"(HK), "n"(K0), "n"(K1), "n"(LIM)
      : "memory");
}

constexpr int NCTA = 128;

constexpr uint32_t OFF_A = 0;
constexpr uint32_t OFF_B = 147456;
constexpr uint32_t OFF_KV = 212992;
constexpr uint32_t OFF_BAR = 231424;
constexpr uint32_t SMEM_BYTES = OFF_BAR + 1024;
enum { B_FULL = 0, B_EMPTY = 4, A_FREE = 8, A_FULL = 17, SIG_KV = 26, SIG_O = 27, SIG_RED = 31, KV_BAR = 32, DUMMY = 38, SIG_KV1 = 39, X_FULL = 40, H0_FULL = 49, XS_FULL = 54, O3_SEEN = 55, PA_DONE = 56, NBAR = 60 };
constexpr int KVH = 64 * 3072;

__device__ __align__(1024) uint8_t g_kv[8 * 260 * 3072];
__device__ __align__(1024) uint8_t g_h[NCTA * 147456];
__device__ __align__(1024) uint8_t g_xn[16 * 147456];
__device__ __align__(1024) uint8_t g_wq[8 * 248832];
__device__ __align__(1024) uint8_t g_o[16 * 147456];
__device__ __align__(1024) uint32_t g_q[(NCTA * 2 * 28 + 12) * 128];
__device__ __align__(1024) float g_dacc[2048 * 576];
__device__ unsigned int g_cnt[(8 + 64 + 16 + 8 + 16 + 16) * 32];
__device__ unsigned int g_epoch[NCTA];
#define STAMP(i) do {} while (0)
#define PSTAMP(i) do {} while (0)
#define PUT(i, v) do {} while (0)
#define PDUMP() do {} while (0)
#define PZERO() do {} while (0)

struct alignas(64) Params {
  CUtensorMap wg, wu, wd, wo, wo_rem, xs, xs_rem, om, om_rem;
  uint32_t zero;
};

#define GW 0
#define GFENCE() do {} while (0)
#define LASTOFF 1
#define PAT 0
#define EARLY_MODE 0
#define EARLY_OK 1
#define BWAIT 1
#define HPF 0
#define HSPLIT 4
#define OSLEEP 0
#define HSLEEP 0
#define NH0 4
#define EDGE 0
#define WPOL 1
#define KPOL 1
#define XPOL 1
#define ZLATE 1
#define H0POL 0
#define OPOL 0
#define FEN 0
#define USE_SS 2
#define SPAT 1
#define DEFER 0
#define RD 0
#define PP_SPLIT 13
constexpr uint32_t SPIN_LIMIT = 1u << 22;

__device__ __forceinline__ void wg_fence() { asm volatile("wgmma.fence.sync.aligned;\n" ::: "memory"); }
__device__ __forceinline__ void wg_commit() { asm volatile("wgmma.commit_group.sync.aligned;\n" ::: "memory"); }
template <int N> __device__ __forceinline__ void wg_wait() { asm volatile("wgmma.wait_group.sync.aligned %0;\n" ::"n"(N) : "memory"); }
__device__ __forceinline__ uint32_t dlo(uint32_t addr, uint32_t lbo) { return ((addr & 0x3FFFF) >> 4) | ((lbo >> 4) << 16); }
constexpr uint32_t dhi(uint32_t sbo, uint32_t mode) { return (sbo >> 4) | (mode << 30); }
constexpr uint32_t H_SW = dhi(1024, 1);
constexpr uint32_t H_NS = dhi(128, 0);
constexpr uint32_t H_K = dhi(384, 0);
constexpr uint32_t H_R = dhi(1024, 0);
constexpr uint32_t H_R2 = dhi(768, 0);
template <int N> __device__ __forceinline__ void regfence(float (&d)[N]) {
#pragma unroll
  for (int i = 0; i < N; i++) asm volatile("" : "+f"(d[i])::"memory");
}
template <int N> __device__ __forceinline__ void regfence(uint32_t (&d)[N]) {
#pragma unroll
  for (int i = 0; i < N; i++) asm volatile("" : "+r"(d[i])::"memory");
}
__device__ __forceinline__ void mbar_init(uint32_t bar, uint32_t cnt) { asm volatile("mbarrier.init.shared::cta.b64 [%0], %1;\n" ::"r"(bar), "r"(cnt) : "memory"); }
__device__ __forceinline__ void mbar_expect(uint32_t bar, uint32_t bytes) { asm volatile("mbarrier.arrive.expect_tx.shared::cta.b64 _, [%0], %1;\n" ::"r"(bar), "r"(bytes) : "memory"); }
__device__ __forceinline__ void mbar_arrive(uint32_t bar) { asm volatile("mbarrier.arrive.shared::cta.b64 _, [%0];\n" ::"r"(bar) : "memory"); }
__device__ __forceinline__ bool mbar_test(uint32_t bar, uint32_t parity) {
  uint32_t ok;
  asm volatile("{\n.reg .pred p;\nmbarrier.test_wait.parity.shared::cta.b64 p, [%1], %2;\nselp.u32 %0, 1, 0, p;\n}\n" : "=r"(ok) : "r"(bar), "r"(parity) : "memory");
  return ok != 0;
}
__device__ __forceinline__ void trap_if(bool cond) {
  asm volatile("{\n.reg .pred p;\nsetp.ne.u32 p, %0, 0;\n@p trap;\n}\n" ::"r"((uint32_t)cond));
}
__device__ __forceinline__ void mbar_wait(uint32_t bar, uint32_t parity) {
  asm volatile(
      "{\n.reg .pred p;\n.reg .u32 n;\nmov.u32 n, 0;\n"
      "LOOP:\nmbarrier.try_wait.parity.shared::cta.b64 p, [%0], %1;\n@p bra DONE;\n"
      "add.u32 n, n, 1;\nsetp.gt.u32 p, n, %2;\n@p trap;\nbra LOOP;\nDONE:\n}\n" ::"r"(bar), "r"(parity), "n"(SPIN_LIMIT) : "memory");
}
__device__ __forceinline__ bool elect_one() {
  uint32_t ok;
  asm volatile("{\n.reg .pred p;\nelect.sync _|p, 0xffffffff;\nselp.u32 %0, 1, 0, p;\n}\n" : "=r"(ok));
  return ok != 0;
}
__device__ __forceinline__ void cluster_arrive() { asm volatile("barrier.cluster.arrive.relaxed.aligned;\n" ::: "memory"); }
__device__ __forceinline__ void cluster_wait() { asm volatile("barrier.cluster.wait.acquire.aligned;\n" ::: "memory"); }
__device__ __forceinline__ void pair_arrive(uint32_t bar, uint32_t rdelta, bool two) {
  if (two) asm volatile("mbarrier.arrive.shared::cluster.b64 _, [%0];\n" ::"r"(bar + rdelta) : "memory");
}
__device__ __forceinline__ void warp_arrive(uint32_t bar) {
  __syncwarp();
  if ((threadIdx.x & 31) == 0) mbar_arrive(bar);
}
__device__ __forceinline__ void named_bar(int id, int n) { asm volatile("bar.sync %0, %1;\n" ::"r"(id), "r"(n) : "memory"); }
__device__ __forceinline__ void tma2d(uint32_t dst, const CUtensorMap* tm, int c0, int c1, uint32_t bar) {
  asm volatile("cp.async.bulk.tensor.2d.shared::cluster.global.mbarrier::complete_tx::bytes [%0], [%1, {%3, %4}], [%2];\n" ::"r"(dst), "l"(tm), "r"(bar), "r"(c0), "r"(c1) : "memory");
}
__device__ __forceinline__ uint64_t pol_stream() {
  uint64_t p;
  asm volatile("createpolicy.fractional.L2::evict_first.b64 %0, 1.0;\n" : "=l"(p));
  return p;
}
__device__ __forceinline__ uint64_t pol_normal() {
  uint64_t p;
  asm volatile("createpolicy.fractional.L2::evict_normal.b64 %0, 1.0;\n" : "=l"(p));
  return p;
}
__device__ __forceinline__ void tma2d_mc(uint32_t dst, const CUtensorMap* tm, int c0, int c1, uint32_t bar, uint64_t pol) {
  asm volatile("cp.async.bulk.tensor.2d.shared::cluster.global.mbarrier::complete_tx::bytes.multicast::cluster.L2::cache_hint [%0], [%1, {%3, %4}], [%2], %6, %5;\n" ::"r"(dst), "l"(tm), "r"(bar), "r"(c0), "r"(c1), "l"(pol), "h"((uint16_t)3) : "memory");
}
__device__ __forceinline__ void tma3d_mc(uint32_t dst, const CUtensorMap* tm, int c0, int c1, int c2, uint32_t bar) {
  asm volatile("cp.async.bulk.tensor.3d.shared::cluster.global.mbarrier::complete_tx::bytes.multicast::cluster [%0], [%1, {%3, %4, %5}], [%2], %6;\n" ::"r"(dst), "l"(tm), "r"(bar), "r"(c0), "r"(c1), "r"(c2), "h"((uint16_t)3) : "memory");
}
__device__ __forceinline__ void bulk_load_s(uint32_t dst, const void* src, uint32_t bytes, uint32_t bar, uint64_t pol) {
  asm volatile("cp.async.bulk.shared::cluster.global.mbarrier::complete_tx::bytes.L2::cache_hint [%0], [%1], %2, [%3], %4;\n" ::"r"(dst), "l"(src), "r"(bytes), "r"(bar), "l"(pol) : "memory");
}
__device__ __forceinline__ void bulk_load_mc(uint32_t dst, const void* src, uint32_t bytes, uint32_t bar, uint64_t pol) {
  asm volatile("cp.async.bulk.shared::cluster.global.mbarrier::complete_tx::bytes.multicast::cluster.L2::cache_hint [%0], [%1], %2, [%3], %5, %4;\n" ::"r"(dst), "l"(src), "r"(bytes), "r"(bar), "l"(pol), "h"((uint16_t)3) : "memory");
}
__device__ __forceinline__ void pf2d(const CUtensorMap* tm, int c0, int c1) {
  asm volatile("cp.async.bulk.prefetch.tensor.2d.L2.global [%0, {%1, %2}];\n" ::"l"(tm), "r"(c0), "r"(c1) : "memory");
}
__device__ __forceinline__ void pf3d(const CUtensorMap* tm, int c0, int c1, int c2) {
  asm volatile("cp.async.bulk.prefetch.tensor.3d.L2.global [%0, {%1, %2, %3}];\n" ::"l"(tm), "r"(c0), "r"(c1), "r"(c2) : "memory");
}
__device__ __forceinline__ void bulk_load(uint32_t dst, const void* src, uint32_t bytes, uint32_t bar) {
  asm volatile("cp.async.bulk.shared::cluster.global.mbarrier::complete_tx::bytes [%0], [%1], %2, [%3];\n" ::"r"(dst), "l"(src), "r"(bytes), "r"(bar) : "memory");
}
__device__ __forceinline__ void pf_bulk(const void* src, uint32_t bytes) {
  asm volatile("cp.async.bulk.prefetch.L2.global [%0], %1;\n" ::"l"(src), "r"(bytes) : "memory");
}
__device__ __forceinline__ void fence_gpu() { asm volatile("fence.acq_rel.gpu;\n" ::: "memory"); }
__device__ __forceinline__ void fence_async_global() { asm volatile("fence.proxy.async.global;\n" ::: "memory"); }
__device__ __forceinline__ void fence_async_smem() { asm volatile("fence.proxy.async.shared::cta;\n" ::: "memory"); }
__device__ __forceinline__ void cnt_signal(unsigned int* p) {
  asm volatile("fence.release.gpu;\nred.relaxed.gpu.global.add.u32 [%0], 1;\n" ::"l"(p) : "memory");
}
__device__ __forceinline__ void cnt_wait(const unsigned int* p, unsigned int target) {
  uint32_t n = 0;
  while (true) {
    unsigned int v;
    asm volatile("ld.relaxed.gpu.global.u32 %0, [%1];\n" : "=r"(v) : "l"(p) : "memory");
    if ((int)(v - target) >= 0) break;
    trap_if(++n > SPIN_LIMIT);
  }
  asm volatile("fence.acquire.gpu;\n" ::: "memory");
}
__device__ __forceinline__ void cnt_wait2(const unsigned int* p, unsigned int tp, const unsigned int* q, unsigned int tq) {
  uint32_t n = 0;
  while (true) {
    unsigned int v, u;
    asm volatile("ld.relaxed.gpu.global.u32 %0, [%1];\n" : "=r"(v) : "l"(p) : "memory");
    asm volatile("ld.relaxed.gpu.global.u32 %0, [%1];\n" : "=r"(u) : "l"(q) : "memory");
    if ((int)((v - tp) | (u - tq)) >= 0) break;
    trap_if(++n > SPIN_LIMIT);
  }
  asm volatile("fence.acquire.gpu;\n" ::: "memory");
}
__device__ __forceinline__ float ex2(float x) { float y; asm volatile("ex2.approx.ftz.f32 %0, %1;\n" : "=f"(y) : "f"(x)); return y; }
__device__ __forceinline__ uint32_t pack(float lo, float hi) { uint32_t r; asm volatile("cvt.rn.bf16x2.f32 %0, %1, %2;\n" : "=r"(r) : "f"(hi), "f"(lo)); return r; }
__device__ __forceinline__ uint32_t pack_relu(float lo, float hi) { uint32_t r; asm volatile("cvt.rn.relu.bf16x2.f32 %0, %1, %2;\n" : "=r"(r) : "f"(hi), "f"(lo)); return r; }
__device__ __forceinline__ uint32_t hmul2(uint32_t a, uint32_t b) { uint32_t r; asm("mul.rn.bf16x2 %0, %1, %2;\n" : "=r"(r) : "r"(a), "r"(b)); return r; }
__device__ __forceinline__ uint32_t hadd2(uint32_t a, uint32_t b) { uint32_t r; asm("add.rn.bf16x2 %0, %1, %2;\n" : "=r"(r) : "r"(a), "r"(b)); return r; }
__device__ __forceinline__ uint32_t hsub2(uint32_t a, uint32_t b) { uint32_t r; asm("sub.rn.bf16x2 %0, %1, %2;\n" : "=r"(r) : "r"(a), "r"(b)); return r; }
__device__ __forceinline__ uint32_t hfma2(uint32_t a, uint32_t b, uint32_t c) { uint32_t r; asm("fma.rn.bf16x2 %0, %1, %2, %3;\n" : "=r"(r) : "r"(a), "r"(b), "r"(c)); return r; }
__device__ __forceinline__ float bf_round(float x) { return __uint_as_float(pack(0.f, x)); }
__device__ __forceinline__ float bf_lo(uint32_t v) { return __uint_as_float(v << 16); }
__device__ __forceinline__ float bf_hi(uint32_t v) { return __uint_as_float(v & 0xffff0000u); }
__device__ __forceinline__ void mma16816(float (&d)[4], uint32_t a0, uint32_t a1, uint32_t a2, uint32_t a3, uint32_t b0, uint32_t b1) {
  asm volatile("mma.sync.aligned.m16n8k16.row.col.f32.bf16.bf16.f32 {%0,%1,%2,%3}, {%4,%5,%6,%7}, {%8,%9}, {%0,%1,%2,%3};\n"
               : "+f"(d[0]), "+f"(d[1]), "+f"(d[2]), "+f"(d[3]) : "r"(a0), "r"(a1), "r"(a2), "r"(a3), "r"(b0), "r"(b1));
}
__device__ __forceinline__ void mma1688(float (&d)[4], uint32_t a0, uint32_t a1, uint32_t b0) {
  asm("mma.sync.aligned.m16n8k8.row.col.f32.bf16.bf16.f32 {%0,%1,%2,%3}, {%4,%5}, {%6}, {%0,%1,%2,%3};\n"
               : "+f"(d[0]), "+f"(d[1]), "+f"(d[2]), "+f"(d[3]) : "r"(a0), "r"(a1), "r"(b0));
}
__device__ __forceinline__ void stg32(void* p, uint32_t v) { asm volatile("st.global.u32 [%0], %1;\n" ::"l"(p), "r"(v) : "memory"); }

template <int I> struct IC { static constexpr int value = I; };
template <int N, int I = 0, typename Fn> __device__ __forceinline__ void static_for(Fn&& f) {
  if constexpr (I < N) { f(IC<I>{}); static_for<N, I + 1>(f); }
}

constexpr uint32_t BF_ONE2 = 0x3f803f80u;
constexpr uint32_t BF_ONE0 = 0x00003f80u;

__device__ __forceinline__ void layer_norm(const uint32_t* x, uint8_t* xn, const uint4* wqkv, uint8_t* wq, unsigned int* cnt, unsigned int* cnt_w, uint32_t sb, int g, int j, int lane) {
  STAMP(26);
  const int row = j * 16 + (threadIdx.x >> 5);
  const uint32_t* xp = (x + (size_t)(g * 128 + j * 16) * 288) + (uint32_t)((threadIdx.x >> 5) * 288 + lane);
  uint32_t w[9];
#pragma unroll
  for (int i = 0; i < 9; i++) w[i] = __ldg(xp + i * 32);
  uint4 wv[2];
  uint32_t wof[2];
#pragma unroll
  for (int i = 0; i < 2; i++) {
    const int u = (threadIdx.x >> 3) + 64 * i, wr = (g + 16 * (u / 18)) * 8 + (threadIdx.x & 7), ch = u % 18;
    wof[i] = wr < 576 ? 82944 + (wr / 48) * 13824 + ch * 768 + (wr % 48) * 16 : 0xffffffffu;
    asm volatile("{\n.reg .pred p;\nsetp.lt.s32 p, %5, 576;\n@p ld.volatile.global.v4.u32 {%0,%1,%2,%3}, [%4];\n}\n" : "=r"(wv[i].x), "=r"(wv[i].y), "=r"(wv[i].z), "=r"(wv[i].w)
                 : "l"(wqkv + wr * 216 + ((ch / 6 + 1) % 3) * 72 + j * 9 + 3 + ch % 6), "r"(wr) : "memory");
  }
  __syncwarp();
  STAMP(27);
  uint8_t* dst = xn + g * 147456 + row * 128 + (((lane >> 2) ^ (row & 7)) << 4) + (lane & 3) * 4;
  float d0[4] = {0.f, 0.f, 0.f, 0.f}, d1[4] = {0.f, 0.f, 0.f, 0.f};
  mma16816(d0, w[0], BF_ONE2, w[1], BF_ONE2, w[0], w[1]);
  mma16816(d1, w[2], BF_ONE2, w[3], BF_ONE2, w[2], w[3]);
  mma16816(d0, w[4], BF_ONE2, w[5], BF_ONE2, w[4], w[5]);
  mma16816(d1, w[6], BF_ONE2, w[7], BF_ONE2, w[6], w[7]);
  mma16816(d0, w[8], BF_ONE2, 0u, BF_ONE2, w[8], 0u);
  float sum = (d0[2] + d1[2]) + (d0[3] + d1[3]);
  float sq = (lane & 3) == (lane >> 3) ? ((lane & 4) ? d0[1] + d1[1] : d0[0] + d1[0]) : 0.f;
  sum += __shfl_xor_sync(0xffffffffu, sum, 1); sum += __shfl_xor_sync(0xffffffffu, sum, 2);
#pragma unroll
  for (int o = 16; o > 0; o >>= 1) sq += __shfl_xor_sync(0xffffffffu, sq, o);
  const float mean = sum * (1.0f / 576.0f);
  float var = fmaxf(sq * (1.0f / 576.0f) - mean * mean, 0.f);
  if (mean * mean > 64.f * var) {
    float a = 0.f;
#pragma unroll 1
    for (int i = 0; i < 9; i++) {
      const uint32_t v = __ldg(xp + i * 32);
      const float l = bf_lo(v) - mean, h = bf_hi(v) - mean;
      a = fmaf(l, l, a); a = fmaf(h, h, a);
    }
#pragma unroll 1
    for (int o = 16; o > 0; o >>= 1) a += __shfl_xor_sync(0xffffffffu, a, o);
    var = a * (1.0f / 576.0f);
  }
  float den, r;
  asm("sqrt.approx.f32 %0, %1;\n" : "=f"(den) : "f"(bf_round(bf_round(var) + 1e-5f)));
  asm("rcp.approx.f32 %0, %1;\n" : "=f"(r) : "f"(bf_round(den)));
  const float rh = bf_round(r);
  const uint32_t m2 = pack(mean, mean), rh2 = pack(rh, rh), rl2 = pack(r - rh, r - rh);
#pragma unroll
  for (int i = 0; i < 9; i++) {
    const uint32_t d = hsub2(w[i], m2);
    stg32(dst + i * 16384, hfma2(d, rh2, hmul2(d, rl2)));
  }
#pragma unroll
  for (int i = 0; i < 2; i++)
    if (wof[i] != 0xffffffffu) *reinterpret_cast<uint4*>(wq + j * 248832 + wof[i]) = wv[i];
  STAMP(28);
  cluster_arrive();
  named_bar(1, 640);
  if (threadIdx.x == 0) {
    cnt_signal(cnt);
    asm volatile("red.relaxed.gpu.global.add.u32 [%0], 1;\n" ::"l"(cnt_w) : "memory");
  }
  STAMP(29);
  __syncwarp();
  cluster_wait();
}

template <int T> __device__ __forceinline__ void kv_store(uint8_t* base, uint32_t lo, uint32_t hi, int c) {
  constexpr int hA = (T >> 1) > 3 ? 3 : (T >> 1), cA = T - 2 * hA;
  {
    uint32_t a = lo, b = hi;
    if (T == 6 && c == 0) { a = BF_ONE0; b = BF_ONE0; }
    uint8_t* p = base + hA * KVH + cA * 128;
    stg32(p, a); stg32(p + 384, b);
  }
  if (T == 2 || T == 4 || T == 6) {
    uint32_t a = lo, b = hi;
    if (c == 3) { a = BF_ONE0; b = BF_ONE0; }
    uint8_t* p = base + (T / 2 - 1) * KVH + 256;
    stg32(p, a); stg32(p + 384, b);
  }
}
constexpr float QSCALE = 0.23570226039551584f * 1.4426950408889634f;

template <int H0, int NH> __device__ __forceinline__ void make_q(uint32_t (&q)[NH][6], const uint32_t* qc, const uint32_t* kc, int lane) {
  const int c = lane & 3;
  const int dl = (lane & ~3) | (lane >> 3);
  const bool od = lane & 4;
  float k1[4] = {0.f, 0.f, 0.f, 0.f}, k2[4] = {0.f, 0.f, 0.f, 0.f};
  mma1688(k1, kc[0], kc[1], kc[0]); mma1688(k2, kc[0], kc[1], kc[1]);
  mma1688(k1, kc[2], kc[3], kc[2]); mma1688(k2, kc[2], kc[3], kc[3]);
  float q0[NH], q1[NH];
#pragma unroll
  for (int h = 0; h < NH; h++) {
#pragma unroll
    for (int i = 0; i < 6; i++) q[h][i] = (i < 2 ? c >= H0 + h : i < 4 ? true : c <= H0 + h) ? qc[4 * h + i] : 0u;
    float n0[4] = {0.f, 0.f, 0.f, 0.f}, n1[4] = {0.f, 0.f, 0.f, 0.f};
#pragma unroll
    for (int i = 0; i < 6; i += 2) { mma1688(n0, q[h][i], q[h][i + 1], q[h][i]); mma1688(n1, q[h][i], q[h][i + 1], q[h][i + 1]); }
    q0[h] = od ? n0[1] : n0[0]; q1[h] = od ? n1[3] : n1[2];
  }
  float kt = __shfl_sync(0xffffffffu, od ? k1[1] + k2[3] : k1[0] + k2[2], dl);
  kt += __shfl_xor_sync(0xffffffffu, kt, 4);
#pragma unroll
  for (int h = 0; h < NH; h++) { q0[h] = __shfl_sync(0xffffffffu, q0[h], dl); q1[h] = __shfl_sync(0xffffffffu, q1[h], dl); }
  kt += __shfl_xor_sync(0xffffffffu, kt, 8);
  kt = (kt + __shfl_xor_sync(0xffffffffu, kt, 16)) * (5.76f / 256.f);
#pragma unroll
  for (int h = 0; h < NH; h++) {
    float r0, r1;
    asm("sqrt.approx.ftz.f32 %0, %1;\n" : "=f"(r0) : "f"(q0[h] * kt));
    asm("sqrt.approx.ftz.f32 %0, %1;\n" : "=f"(r1) : "f"(q1[h] * kt));
    const uint32_t b0 = pack(-85.f - r0, 0.f), b1 = pack(-85.f - r1, 0.f);
    if (H0 + h < 3) { q[h][4] = c == 3 ? b0 : q[h][4]; q[h][5] = c == 3 ? b1 : q[h][5]; }
    else { q[h][0] = c == 0 ? b0 : q[h][0]; q[h][1] = c == 0 ? b1 : q[h][1]; }
  }
}

__device__ __forceinline__ void attn_exact(const uint8_t* kvh, const uint32_t* qin, float* oout, int lane) {
  const int c = lane & 3;
  uint32_t q[6];
#pragma unroll
  for (int i = 0; i < 6; i++) q[i] = qin[i];
  float o[3][4];
#pragma unroll
  for (int i = 0; i < 3; i++) { o[i][0] = o[i][1] = o[i][2] = o[i][3] = 0.f; }
  float m0 = -INFINITY, m1 = -INFINITY;
  for (int i = 0; i < 128; i++) {
    const uint8_t* kb = kvh + (i >> 1) * 3072 + (i & 1) * 768;
    float s[2][4];
#pragma unroll
    for (int nt = 0; nt < 2; nt++) {
      const uint32_t* p = reinterpret_cast<const uint32_t*>(kb + nt * 384) + lane;
      uint32_t b0 = __ldcg(p), b1 = __ldcg(p + 32), b2 = __ldcg(p + 64);
      s[nt][0] = s[nt][1] = s[nt][2] = s[nt][3] = 0.f;
      mma16816(s[nt], q[0], q[1], q[2], q[3], b0, b1);
      mma16816(s[nt], q[4], q[5], 0u, 0u, b2, 0u);
    }
    float a0 = fmaxf(fmaxf(s[0][0], s[0][1]), fmaxf(s[1][0], s[1][1]));
    float a1 = fmaxf(fmaxf(s[0][2], s[0][3]), fmaxf(s[1][2], s[1][3]));
    a0 = fmaxf(a0, __shfl_xor_sync(0xffffffffu, a0, 1)); a0 = fmaxf(a0, __shfl_xor_sync(0xffffffffu, a0, 2));
    a1 = fmaxf(a1, __shfl_xor_sync(0xffffffffu, a1, 1)); a1 = fmaxf(a1, __shfl_xor_sync(0xffffffffu, a1, 2));
    const float n0 = fmaxf(m0, a0), n1 = fmaxf(m1, a1);
    const float al0 = ex2(m0 - n0), al1 = ex2(m1 - n1);
    m0 = n0; m1 = n1;
    const uint32_t p0 = pack(ex2(s[0][0] - n0), ex2(s[0][1] - n0)), p1 = pack(ex2(s[0][2] - n1), ex2(s[0][3] - n1));
    const uint32_t p2 = pack(ex2(s[1][0] - n0), ex2(s[1][1] - n0)), p3 = pack(ex2(s[1][2] - n1), ex2(s[1][3] - n1));
#pragma unroll
    for (int cc = 0; cc < 3; cc++) {
      const unsigned short* vp = reinterpret_cast<const unsigned short*>(kb + 4608 + cc * 128 + c * 32) + (lane >> 2);
      const uint32_t b0 = (uint32_t)__ldcg(vp) | ((uint32_t)__ldcg(vp + 8) << 16);
      const uint32_t b1 = (uint32_t)__ldcg(vp + 192) | ((uint32_t)__ldcg(vp + 200) << 16);
      o[cc][0] *= al0; o[cc][1] *= al0; o[cc][2] *= al1; o[cc][3] *= al1;
      mma16816(o[cc], p0, p1, p2, p3, b0, b1);
    }
  }
#pragma unroll
  for (int i = 0; i < 12; i++) oout[i] = o[i >> 2][i & 3];
}

struct Ring { uint32_t dB, bars, rdelta; bool leader, two; };
template <int OFF> __device__ __forceinline__ void ldsm(uint32_t (&r)[4], uint32_t a) {
  asm volatile("ldmatrix.sync.aligned.m8n8.x4.shared.b16 {%0,%1,%2,%3}, [%4 + %5];\n" : "=r"(r[0]), "=r"(r[1]), "=r"(r[2]), "=r"(r[3]) : "r"(a), "n"(OFF) : "memory");
}
template <bool DEEP, bool ZERO, int O1, int O2, int O3, int ON, typename S1, typename S2, typename S3>
__device__ __forceinline__ void k_block128(float (&acc)[64], uint32_t (&x)[4], uint32_t a1, uint32_t a2, uint32_t a3, uint32_t an, int nz,
                                           uint32_t& it, const Ring& R, S1&& s1, S2&& s2, S3&& s3) {
  const uint32_t db = R.dB + (it & 3) * 1024;
  uint32_t y[4];
  it++;
  wg_wait<0>();
  wg_fence();
  if constexpr (ZERO) wgmma_rs_n128_tb_p<H_SW, 0>(acc, x[0], x[1], x[2], x[3], db, nz);
  else wgmma_rs_n128_tb<H_SW, 0>(acc, x[0], x[1], x[2], x[3], db);
  wg_commit();
  ldsm<O1>(y, a1);
  if (!DEEP) { s1(); wg_wait<0>(); }
  wg_fence();
  wgmma_rs_n128_tb<H_SW, 128>(acc, y[0], y[1], y[2], y[3], db);
  wg_commit();
  if (DEEP) { s1(); s2(); wg_wait<1>(); }
  ldsm<O2>(x, a2);
  if (!DEEP) s2();
  wg_wait<0>();
  wg_fence();
  wgmma_rs_n128_tb<H_SW, 256>(acc, x[0], x[1], x[2], x[3], db);
  wg_commit();
  ldsm<O3>(y, a3);
  s3();
  wg_wait<0>();
  wg_fence();
  wgmma_rs_n128_tb<H_SW, 384>(acc, y[0], y[1], y[2], y[3], db);
  wg_commit();
  ldsm<ON>(x, an);
  mbar_wait(R.bars + 8 * (B_FULL + (it & 3)), (it >> 2) & 1);
}
template <uint32_t HA, int KS, int OA, bool ZERO, typename S1, typename S2, typename S3>
__device__ __forceinline__ void k_block128s(float (&acc)[64], uint32_t da, int nz, uint32_t& it, const Ring& R, S1&& s1, S2&& s2, S3&& s3) {
  const uint32_t db = R.dB + (it & 3) * 1024;
  it++;
  wg_wait<0>();
  wg_fence();
  if constexpr (ZERO) wgmma_ss_n128_tb_p<HA, H_SW, OA, 0>(acc, da, db, nz);
  else wgmma_ss_n128_tb<HA, H_SW, OA, 0>(acc, da, db);
  wg_commit();
  s1();
  wg_wait<0>();
  wg_fence();
  wgmma_ss_n128_tb<HA, H_SW, OA + KS, 128>(acc, da, db);
  wg_commit();
  s2();
  wg_wait<0>();
  wg_fence();
  wgmma_ss_n128_tb<HA, H_SW, OA + 2 * KS, 256>(acc, da, db);
  if (SPAT == 0) { wg_commit(); wg_wait<0>(); }
  wgmma_ss_n128_tb<HA, H_SW, OA + 3 * KS, 384>(acc, da, db);
  wg_commit();
  s3();
  mbar_wait(R.bars + 8 * (B_FULL + (it & 3)), (it >> 2) & 1);
}
__device__ __forceinline__ void release_prev(uint32_t it, int back, const Ring& R, bool cond) {
  pair_arrive(R.bars + 8 * (B_EMPTY + ((it - back) & 3)), R.rdelta, R.two && cond);
}
template <uint32_t HA, int KS, bool ZERO, int NA, typename Hook>
__device__ __forceinline__ void k_loop64(float (&acc)[NA], uint32_t da, int kb0, int kb1, uint32_t& it, const Ring& R,
                                         uint32_t afree, uint32_t astep, Hook&& hook) {
  da += kb0 * 1024;
#pragma unroll 1
  for (int kb = kb0; kb < kb1; kb++) {
    const uint32_t st = it & 3;
    const uint32_t db = R.dB + st * 1024 + (kb & 1) * 512;
    wg_wait<0>();
    wg_fence();
    if constexpr (ZERO) wgmma_ss_n64_tb_p<HA, H_SW, 0, 0>(acc, da, db, kb - kb0);
    else wgmma_ss_n64_tb<HA, H_SW, 0, 0>(acc, da, db);
    wgmma_ss_n64_tb<HA, H_SW, KS, 128>(acc, da, db);
    wg_commit();
    pair_arrive(R.bars + 8 * (B_EMPTY + ((st - 1) & 3)), R.rdelta, R.two && kb > kb0 && (kb & 1) == 0);
    if (R.leader && kb > kb0) mbar_arrive(afree);
    if (kb > kb0) afree += astep;
    hook(kb, IC<0>{});
    wg_wait<0>();
    wg_fence();
    wgmma_ss_n64_tb<HA, H_SW, 2 * KS, 256>(acc, da, db);
    wgmma_ss_n64_tb<HA, H_SW, 3 * KS, 384>(acc, da, db);
    wg_commit();
    hook(kb, IC<1>{});
    da += 1024;
    if ((kb & 1) || kb == 8) {
      it++;
      mbar_wait(R.bars + 8 * (B_FULL + (it & 3)), (it >> 2) & 1);
    }
    hook(kb, IC<2>{});
  }
  wg_wait<0>();
  pair_arrive(R.bars + 8 * (B_EMPTY + ((it - 1) & 3)), R.rdelta, R.two);
  regfence(acc);
}
template <int OFF> __device__ __forceinline__ void stg_at(void* p, uint32_t v) {
  asm volatile("st.global.u32 [%0 + %2], %1;\n" ::"l"(p), "r"(v), "n"(OFF) : "memory");
}
template <int OFF> __device__ __forceinline__ uint32_t ldcg_at(const void* p) {
  uint32_t v;
  asm volatile("ld.global.cg.u32 %0, [%1 + %2];\n" : "=r"(v) : "l"(p), "n"(OFF) : "memory");
  return v;
}
__device__ __forceinline__ uint32_t tid_now() { uint32_t t; asm volatile("mov.u32 %0, %%tid.x;\n" : "=r"(t)); return t; }
__device__ __forceinline__ float mov_f(float x) { float y; asm volatile("mov.b32 %0, %1;\n" : "=f"(y) : "f"(x)); return y; }
template <int WHEN, int OFF> __device__ __forceinline__ void red4_at(int sel, float* p, float a, float b, float c, float d) {
  asm volatile("{\n.reg .pred p;\nsetp.eq.s32 p, %5, %6;\n@p red.global.add.v4.f32 [%0 + %7], {%1,%2,%3,%4};\n}\n" ::"l"(p), "f"(a), "f"(b), "f"(c), "f"(d), "r"(sel), "n"(WHEN), "n"(OFF) : "memory");
}

#define PFD 2
__device__ __forceinline__ void prefetch_tile(const Params& P, int T, int g, int j) {
  for (int idx = g; idx < 18; idx += 16) {
    const int kb = idx >> 1, u = idx & 1;
    if (T < 9) pf2d(u ? &P.wu : &P.wg, j * 576 + T * 64, kb * 64);
    else if (T < 14) { if (T < 13 || u == 0) pf2d(&P.wd, ((j + 2 * (T - 9) + 1 + u) % 9) * 64, j * 576 + kb * 64); }
    else if (T == 14) pf3d(&P.wo, u ? 512 : j * 64, kb * 8, 0);
  }
}

__global__ void __cluster_dims__(2, 1, 1) __launch_bounds__(640, 1) fused_kernel(const uint32_t* __restrict__ a_x, const uint4* __restrict__ a_wqkv,
    uint8_t* a_xn, uint8_t* a_wq, unsigned int* a_cnt, const __grid_constant__ Params P) {
  extern __shared__ __align__(1024) uint8_t smem[];
  const int g = blockIdx.x & 15, j = blockIdx.x >> 4;
  const int lane = threadIdx.x & 31;
  const uint32_t sb = __shfl_sync(0xffffffffu, (uint32_t)__cvta_generic_to_shared(smem), 0);
  STAMP(31);
  const int wg = __shfl_sync(0xffffffffu, (int)threadIdx.x >> 7, 0);
  unsigned int* const cnt_xn = a_cnt + (96 + g) * 32;
  unsigned int* const cnt_wq = a_cnt + (112 + j) * 32;
  uint4 wv[3];
  uint32_t wof[3];
  if (wg < 4) layer_norm(a_x, a_xn, a_wqkv, a_wq, cnt_xn, cnt_wq, sb, g, j, lane);
  else {
#pragma unroll
    for (int i = 0; i < 3; i++) {
      const int u = ((threadIdx.x - 512) >> 3) + 16 * i, wr = (g + 16 * (u / 9)) * 8 + (threadIdx.x & 7), ch = u % 9;
      wof[i] = wr < 576 ? (wr >> 6) * 9216 + ch * 1024 + (wr & 63) * 16 : 0xffffffffu;
      asm volatile("ld.global.nc.L1::no_allocate.v4.u32 {%0,%1,%2,%3}, [%4];\n" : "=r"(wv[i].x), "=r"(wv[i].y), "=r"(wv[i].z), "=r"(wv[i].w)
                   : "l"(a_wqkv + min(wr, 575) * 216 + (ch / 3) * 72 + j * 9 + ch % 3) : "memory");
    }
  }
  PZERO();
  PUT(23, gtime());
  const uint32_t bars = sb + OFF_BAR;
  const int rank = blockIdx.x & 1;
  const int c = lane & 3;
  uint32_t rdelta;
  asm volatile("mapa.shared::cluster.u32 %0, %1, %2;\n" : "=r"(rdelta) : "r"(bars), "r"(lane == 1 ? rank ^ 1 : rank));
  rdelta -= bars;
  const bool two = lane < 2;
  unsigned int* const cnt_kv = a_cnt + j * 32;
  unsigned int* const cnt_o = a_cnt + (8 + g * 4) * 32;
  unsigned int* const cnt_red = a_cnt + (72 + g) * 32;

  if (wg < 2) {
    asm volatile("setmaxnreg.inc.sync.aligned.u32 120;\n");
    const int wq = ((int)threadIdx.x >> 5) & 3;
    STAMP(0);
    const int half = wg;
    const uint32_t dA_sw = dlo(sb + OFF_A + half * 8192, 16);
    const uint32_t dA_ns = dlo(sb + OFF_A + half * 8192, 1024);
    const uint32_t dB = dlo(sb + OFF_B, 8192);
    const unsigned int ep1 = *(volatile unsigned int*)(g_epoch + blockIdx.x) + 1;
    const bool leader = elect_one();
    const uint32_t dummy = bars + 8 * DUMMY;
    uint32_t it = 0;
    const Ring R = {dB, bars, rdelta, leader, two};
    float* const dacc_w = g_dacc + (size_t)((g * 8 + half * 4 + wq) * 72) * 128 + lane * 4;
    {
      float a0[36], a1[36];
#pragma unroll
      for (int i = 0; i < 36; i++) { a0[i] = 0.f; a1[i] = 0.f; }
      const uint32_t dR = dlo(sb + OFF_B, 128);
      regfence(a0); regfence(a1);
      mbar_wait(bars + 8 * PA_DONE, 0);
      uint32_t* qg = g_q + (size_t)(blockIdx.x * 2 + half) * 28 * 128 + (threadIdx.x & 127);
      uint32_t qc[14], kc[14];
#pragma unroll 1
      for (int r = 0; r < 3; r++) {
        const uint32_t da = dA_sw + r * 3072;
        if (r == 2) {
          mbar_wait(bars + 8 * SIG_KV, 0);
          qc[0] = ldcg_at<24 * 512>(qg); qc[1] = ldcg_at<25 * 512>(qg);
        }
        static_for<4>([&](auto ST) {
          constexpr int st = decltype(ST)::value;
          if (st < 3) mbar_wait(bars + 8 * (X_FULL + 3 * r + st), 0);
          mbar_wait(bars + 8 * (B_FULL + st), r & 1);
          if (st == 0 && r == 0) STAMP(25);
          wg_fence();
          static_for<3>([&](auto KS) {
            constexpr int ks = 3 * st + decltype(KS)::value, oa = (ks >> 2) * 1024 + (ks & 3) * 2, ob = st * 1024 + decltype(KS)::value * 16;
            wgmma_ss_n72_tb<H_SW, H_R2, oa, ob>(a0, da, dR);
            wgmma_ss_n72_tb<H_SW, H_R2, oa, ob + 432>(a1, da, dR);
          });
          wg_commit();
          wg_wait<1>();
          pair_arrive(bars + 8 * (B_EMPTY + ((st + 3) & 3)), rdelta, two && (st > 0 || r > 0));
        });
      }
      wg_wait<0>();
      pair_arrive(bars + 8 * (B_EMPTY + 3), rdelta, two);
      regfence(a0); regfence(a1);
      it = 12;
      STAMP(1);
      uint8_t* base = g_kv + (size_t)(j * 260 + 1 + 4 * g + 2 * half + (wq >> 1)) * 3072 + 1536 + (wq & 1) * 768 + lane * 4;
#pragma unroll
      for (int i = 0; i < 12; i++) {
        kc[2 + i] = pack(a0[2 * i], a0[2 * i + 1]);
        qc[2 + i] = pack(a1[12 + 2 * i] * QSCALE, a1[13 + 2 * i] * QSCALE);
      }
      uint32_t qo[3][6];
      make_q<1, 3>(qo, qc, kc + 6, lane);
      STAMP(30);
      static_for<6>([&](auto I_) {
        constexpr int I = decltype(I_)::value;
        kv_store<I + 3>(base, kc[2 + 2 * I], kc[3 + 2 * I], c);
        if constexpr (I < 3) kv_store<I + 3>(base + 4608, pack(a0[24 + 4 * I], a0[25 + 4 * I]), pack(a0[26 + 4 * I], a0[27 + 4 * I]), c);
        else kv_store<I + 3>(base + 4608, pack(a1[4 * I - 12], a1[4 * I - 11]), pack(a1[4 * I - 10], a1[4 * I - 9]), c);
      });
#pragma unroll
      for (int i = 0; i < 18; i++) stg32(qg + (6 + i) * 128, qo[i / 6][i % 6]);
      warp_arrive(bars + 8 * SIG_KV1);
      mbar_wait(bars + 8 * B_FULL, 1);
      STAMP(2);
    }
    float own[32];
    {
      float acc[64];
#pragma unroll
      for (int i = 0; i < 64; i++) acc[i] = 0.f;
      uint8_t* hp = g_h + (size_t)blockIdx.x * 147456 + half * 8192 + wq * 256 + lane * 4 - 16384;
      uint32_t hv[16];
#pragma unroll
      for (int i = 0; i < 16; i++) hv[i] = 0u;
      const uint32_t fa = sb + OFF_A + half * 8192 + (wq * 16 + (lane & 15)) * 128 + (((lane >> 4) ^ (lane & 7)) << 4);
      uint32_t xf[4];
      ldsm<0>(xf, fa);
#pragma unroll 1
      for (int t = 0; t < 9; t++) {
        {
          uint32_t afree = t == 8 ? bars + 8 * A_FREE - 8 : dummy;
          const uint32_t astep = t == 8 ? 8 : 0;
          uint32_t ko = 0;
#pragma unroll 1
          for (int kb = 0; kb < 9; kb++) {
            const uint32_t kn = kb < 8 ? ko + 16384 : (t == 8 ? ko : 0);
            auto put = [&](auto S_) {
              constexpr int sh = decltype(S_)::value;
              if (!DEFER) return;
              if (kb == 0) { if (t > 0) static_for<3>([&](auto I) { constexpr int i = 3 * sh + decltype(I)::value; stg_at<(i >> 1) * 1024 + (i & 1) * 128>(hp, hv[i]); }); }
              else if (kb == 1) { if (t > 0) static_for<3>([&](auto I) { constexpr int i = 9 + 3 * sh + decltype(I)::value; if constexpr (i < 16) stg_at<(i >> 1) * 1024 + (i & 1) * 128>(hp, hv[i]); }); }
            };
            k_block128<(RD & 1) != 0, true, 0, 0, 0, 0>(acc, xf, (fa ^ 32) + ko, (fa ^ 64) + ko, (fa ^ 96) + ko, fa + kn, kb, it, R,
                                         [&] { release_prev(it, 2, R, kb > 0); put(IC<0>{}); },
                                         [&] { put(IC<1>{}); },
                                         [&] { put(IC<2>{}); __syncwarp(); if (leader && kb > 0) mbar_arrive(afree); afree += astep; });
            ko = kn;
          }
          wg_wait<0>();
          release_prev(it, 1, R, true);
          regfence(acc);
        }
#pragma unroll
        for (int i = 0; i < 16; i++) hv[i] = hmul2(pack_relu(acc[2 * i], acc[2 * i + 1]), pack(acc[32 + 2 * i], acc[33 + 2 * i]));
        hp += 16384;
        if (t < 8) {
          if (!DEFER) static_for<16>([&](auto I) { constexpr int i = decltype(I)::value; stg_at<(i >> 1) * 1024 + (i & 1) * 128>(hp, hv[i]); });
        } else {
          named_bar(3 + half, 128);
          const uint32_t sp = sb + OFF_A + 8 * 16384 + half * 8192 + wq * 256 + lane * 4;
#pragma unroll
          for (int i = 0; i < 16; i++) asm volatile("st.shared.b32 [%0], %1;\n" ::"r"(sp + (i >> 1) * 1024 + (i & 1) * 128), "r"(hv[i]) : "memory");
          fence_async_smem();
          named_bar(3 + half, 128);
        }
        STAMP(3 + t);
      }
      float hold[32];
      float* hp2 = dacc_w;
      auto red_hold = [&](auto I) {
        constexpr int i = decltype(I)::value;
        if constexpr (i < 8)
          asm volatile("red.global.add.v4.f32 [%0 + %5], {%1,%2,%3,%4};\n" ::"l"(hp2), "f"(hold[4 * i]), "f"(hold[4 * i + 1]), "f"(hold[4 * i + 2]), "f"(hold[4 * i + 3]), "n"(i * 512) : "memory");
      };
      mbar_wait(bars + 8 * A_FULL, 0);
      {
        float t32[32];
#pragma unroll
        for (int i = 0; i < 32; i++) t32[i] = 0.f;
        k_loop64<H_NS, 128, false>(t32, dA_ns, 0, 4, it, R, dummy, 0, [&](int kb, auto POS) {
          if constexpr (decltype(POS)::value == 2) mbar_wait(bars + 8 * (A_FULL + kb + 1), 0);
        });
#pragma unroll
        for (int i = 0; i < 32; i++) { acc[i] = mov_f(t32[i]); acc[32 + i] = 0.f; hold[i] = 0.f; }
      }
      const uint32_t fh = sb + OFF_A + half * 8192 + (lane >> 4) * 1024 + (wq * 16 + (lane & 15)) * 16;
      ldsm<4 * 16384>(xf, fh);
      int p = j;
#pragma unroll 1
      for (int tp = 0;; tp++) {
        regfence(acc);
        static_for<5>([&](auto U) {
          constexpr int u = decltype(U)::value, o = (4 + u) * 16384;
          k_block128s<H_NS, 128, o / 16, false>(acc, dA_ns, 0, it, R,
              [&] { release_prev(it, 2, R, u > 0); red_hold(IC<2 * u>{}); }, [&] { red_hold(IC<2 * u + 1>{}); },
              [&] { if (u < 3) mbar_wait(bars + 8 * (A_FULL + 5 + u), 0); });
        });
        wg_wait<0>();
        release_prev(it, 1, R, true);
        regfence(acc);
#pragma unroll
        for (int i = 0; i < 32; i++) { hold[i] = mov_f(acc[i]); acc[i] = 0.f; }
        p = p == 8 ? 0 : p + 1; hp2 = dacc_w + p * 1024;
        regfence(acc);
        static_for<4>([&](auto U) {
          constexpr int u = decltype(U)::value, o = u * 16384;
          k_block128s<H_NS, 128, o / 16, false>(acc, dA_ns, 0, it, R,
              [&] { release_prev(it, 2, R, u > 0); red_hold(IC<2 * u>{}); },
              [&] { red_hold(IC<2 * u + 1>{}); if (u > 0 && leader && tp == 3) mbar_arrive(bars + 8 * (A_FREE + u - 1)); }, [&] {});
        });
        wg_wait<0>();
        release_prev(it, 1, R, true);
        if (leader && tp == 3) mbar_arrive(bars + 8 * (A_FREE + 3));
        regfence(acc);
        p = p == 8 ? 0 : p + 1; hp2 = dacc_w + p * 1024;
        STAMP(12 + tp);
#pragma unroll
        for (int i = 0; i < 32; i++) hold[i] = mov_f(acc[32 + i]);
        if (tp == 3) break;
#pragma unroll
        for (int i = 0; i < 32; i++) acc[32 + i] = 0.f;
      }
#pragma unroll
      for (int i = 0; i < 32; i++) own[i] = mov_f(acc[i]);
      k_loop64<H_NS, 128, false>(own, dA_ns, 4, 9, it, R, bars + 8 * (A_FREE + 4), 8, [&](int kb, auto POS) {
        constexpr int pos = decltype(POS)::value;
        if constexpr (pos < 2) {
          static_for<4>([&](auto I) {
            constexpr int i = 2 * decltype(I)::value + pos;
            red4_at<(i >> 1) + 4, i * 512>(kb, hp2, hold[4 * i], hold[4 * i + 1], hold[4 * i + 2], hold[4 * i + 3]);
          });
        }
        if constexpr (pos == 1) { __syncwarp(); if (leader && kb == 7) mbar_arrive(bars + 8 * SIG_RED); }
      });
      if (leader) mbar_arrive(bars + 8 * (A_FREE + 8));
    }
    STAMP(16);
    {
      float acc[36];
#pragma unroll
      for (int i = 0; i < 36; i++) acc[i] = 0.f;
      auto wo_issue = [&](int t) {
        const uint32_t st = it & 3;
        mbar_wait(bars + 8 * (B_FULL + st), (it >> 2) & 1);
        mbar_wait(bars + 8 * (A_FULL + t), t < 8 ? 1 : 0);
        wg_fence();
        static_for<4>([&](auto KS) { constexpr int ks = decltype(KS)::value; wgmma_ss_n72_tb<H_NS, H_SW, ks * 128, ks * 128>(acc, dA_ns + t * 1024, dB + st * 1024); });
        wg_commit();
        it++;
      };
      regfence(acc);
#pragma unroll 1
      for (int t = 0; t < 6; t++) {
        wo_issue(t);
        wg_wait<1>();
        pair_arrive(bars + 8 * (B_EMPTY + ((it - 2) & 3)), rdelta, two && t > 0);
      }
      auto last_ready = [&](uint32_t bar, uint32_t parity) -> bool {
        uint32_t r;
        asm volatile("{\n.reg .pred p, q;\nsetp.ne.u32 p, %1, 0;\nbar.red.and.pred q, %2, 128, p;\nselp.u32 %0, 1, 0, q;\n}\n"
                     : "=r"(r) : "r"((uint32_t)mbar_test(bar, parity)), "r"(3 + half) : "memory");
        return __shfl_sync(0xffffffffu, r, 0) != 0;
      };
      int tn = 6;
      if (last_ready(bars + 8 * (A_FULL + 6), 1)) {
#pragma unroll 1
        for (; tn < 9; tn++) wo_issue(tn);
      }
      wg_wait<0>();
      regfence(acc);
      STAMP(17);
      if (lane == 0) cnt_wait(cnt_red, 8 * ep1);
      __syncwarp();
      STAMP(18);
      float dv[36];
      static_for<9>([&](auto I) {
        constexpr int i = decltype(I)::value;
        asm volatile("ld.global.cg.v4.f32 {%0,%1,%2,%3}, [%4 + %5];\n" : "=f"(dv[4 * i]), "=f"(dv[4 * i + 1]), "=f"(dv[4 * i + 2]), "=f"(dv[4 * i + 3])
                     : "l"(i < 8 ? dacc_w + j * 1024 : dacc_w + (64 + j) * 128), "n"(i < 8 ? i * 512 : 0) : "memory");
      });
      const bool e2 = last_ready(bars + 8 * O3_SEEN, 0) && tn < 9;
      uint32_t gv[18];
      auto gate = [&](auto I0, auto I1) {
#pragma unroll
        for (int i = decltype(I0)::value; i < decltype(I1)::value; i++) {
          const uint32_t d2 = i < 16 ? pack(dv[2 * i] + own[(2 * i) & 31], dv[2 * i + 1] + own[(2 * i + 1) & 31]) : pack(dv[2 * i], dv[2 * i + 1]);
          const float a = bf_lo(d2), b = bf_hi(d2);
          float ra, rb;
          asm("rcp.approx.ftz.f32 %0, %1;\n" : "=f"(ra) : "f"(1.0f + ex2(a * -1.4426950408889634f)));
          asm("rcp.approx.ftz.f32 %0, %1;\n" : "=f"(rb) : "f"(1.0f + ex2(b * -1.4426950408889634f)));
          gv[i] = pack(a * ra, b * rb);
        }
      };
      if (e2) {
#pragma unroll 1
        for (; tn < 9; tn++) wo_issue(tn);
      }
      STAMP(22);
      gate(IC<0>{}, IC<18>{});
      STAMP(19);
#pragma unroll 1
      for (; tn < 9; tn++) wo_issue(tn);
      mbar_wait(bars + 8 * XS_FULL, 0);
      const uint32_t r8 = lane >> 2;
      const uint32_t sm = sb + OFF_KV + half * 8192 + (wq * 16 + r8) * 128 + c * 4;
      const uint32_t sr = sb + OFF_KV + 16384 + half * 1024 + wq * 256 + lane * 4;
      uint32_t xv[18];
#pragma unroll
      for (int i = 0; i < 9; i++) {
        const uint32_t a0 = i < 8 ? sm + ((i ^ r8) << 4) : sr, a1 = a0 + (i < 8 ? 1024 : 128);
        asm volatile("ld.shared.b32 %0, [%1];\n" : "=r"(xv[2 * i]) : "r"(a0) : "memory");
        asm volatile("ld.shared.b32 %0, [%1];\n" : "=r"(xv[2 * i + 1]) : "r"(a1) : "memory");
      }
      wg_wait<0>();
      regfence(acc);
      STAMP(20);
#pragma unroll
      for (int i = 0; i < 9; i++) {
        const uint32_t a0 = i < 8 ? sm + ((i ^ r8) << 4) : sr, a1 = a0 + (i < 8 ? 1024 : 128);
        asm volatile("st.shared.b32 [%0], %1;\n" ::"r"(a0), "r"(hadd2(xv[2 * i], hmul2(pack(acc[4 * i], acc[4 * i + 1]), gv[2 * i]))) : "memory");
        asm volatile("st.shared.b32 [%0], %1;\n" ::"r"(a1), "r"(hadd2(xv[2 * i + 1], hmul2(pack(acc[4 * i + 2], acc[4 * i + 3]), gv[2 * i + 1]))) : "memory");
      }
      STAMP(24);
      fence_async_smem();
      named_bar(3 + half, 128);
      if (wq == 0 && leader) {
        asm volatile("cp.async.bulk.tensor.2d.global.shared::cta.bulk_group [%0, {%2, %3}], [%1];\n" ::"l"(&P.om), "r"(sb + OFF_KV + half * 8192), "r"(j * 64), "r"(g * 128 + half * 64) : "memory");
        asm volatile("cp.async.bulk.tensor.2d.global.shared::cta.bulk_group [%0, {%2, %3}], [%1];\n" ::"l"(&P.om_rem), "r"(sb + OFF_KV + 16384 + half * 1024), "r"(512 + j * 8), "r"(g * 128 + half * 64) : "memory");
        asm volatile("cp.async.bulk.commit_group;\ncp.async.bulk.wait_group.read 0;\n" ::: "memory");
      }
      STAMP(21);
      PUT(22, gtime());
      if (threadIdx.x == 0) g_epoch[blockIdx.x] = ep1;
    }
    __syncwarp();
    cluster_arrive();
    cluster_wait();
  } else if (wg < 4) {
    asm volatile("setmaxnreg.inc.sync.aligned.u32 104;\n");
    const int wq = ((int)threadIdx.x >> 5) & 3;
    STAMP(0);
    const int half = wg - 2;
    uint32_t* const qg = g_q + (size_t)(blockIdx.x * 2 + half) * 28 * 128 + (threadIdx.x & 127);
    uint32_t qn[6];
    {
      const uint32_t dA_sw = dlo(sb + OFF_A + half * 8192, 16);
      const uint32_t dR = dlo(sb + OFF_B, 128);
      float acc[36];
#pragma unroll
      for (int i = 0; i < 36; i++) acc[i] = 0.f;
#pragma unroll 1
      for (int kb = 0; kb < 9; kb++) {
        if ((kb & 1) == 0) mbar_wait(bars + 8 * (H0_FULL + (kb >> 1)), 0);
        mbar_wait(bars + 8 * (X_FULL + kb), 0);
        regfence(acc);
        wg_fence();
        static_for<4>([&](auto KS) { constexpr int ks = decltype(KS)::value; wgmma_ss_n72_tb<H_SW, H_R, ks * 2, ks * 16>(acc, dA_sw + kb * 1024, dR + kb * 576); });
        wg_commit();
        wg_wait<1>();
        STAMP(10 + kb);
        pair_arrive(bars + 8 * (B_EMPTY + (kb >> 1) - 1), rdelta, two && (kb & 1) == 0 && kb >= 2 && kb < 8);
      }
      wg_wait<0>();
      pair_arrive(bars + 8 * (B_EMPTY + 3), rdelta, two);
      if (lane == 0) mbar_arrive(bars + 8 * PA_DONE);
      regfence(acc);
      STAMP(8);
      uint8_t* base = g_kv + (size_t)(j * 260 + 1 + 4 * g + 2 * half + (wq >> 1)) * 3072 + 1536 + (wq & 1) * 768 + lane * 4;
      uint32_t qw[6], kw[6];
#pragma unroll
      for (int i = 0; i < 6; i++) { kw[i] = pack(acc[12 + 2 * i], acc[13 + 2 * i]); qw[i] = pack(acc[2 * i] * QSCALE, acc[2 * i + 1] * QSCALE); }
      static_for<3>([&](auto I_) {
        constexpr int I = decltype(I_)::value;
        kv_store<I>(base, kw[2 * I], kw[2 * I + 1], c);
        kv_store<I>(base + 4608, pack(acc[24 + 4 * I], acc[25 + 4 * I]), pack(acc[26 + 4 * I], acc[27 + 4 * I]), c);
      });
      stg32(qg + 24 * 128, qw[4]); stg32(qg + 25 * 128, qw[5]);
      warp_arrive(bars + 8 * SIG_KV);
      STAMP(9);
      uint32_t q1[1][6];
      make_q<0, 1>(q1, qw, kw, lane);
#pragma unroll
      for (int i = 0; i < 6; i++) { qn[i] = q1[0][i]; stg32(qg + i * 128, qn[i]); }
    }
    STAMP(1);
    const uint32_t dV = dlo(sb + OFF_KV, 384);
    constexpr int K0 = (1536 >> 4) - ((384 - 128) >> 4 << 16);
    constexpr int K1 = ((1536 + 256) >> 4) - (384 >> 4 << 16);
    uint32_t q[8];
    float sa[16], o[12];
    uint32_t pb[8];
    const uint32_t kb0 = bars + 8 * KV_BAR;
    uint32_t w = dV + 384, wp = dV, kb = kb0 + 16, kp = kb0, ph = 0;
    const uint32_t vz = P.zero & threadIdx.x;
    const uint32_t* qp = qg;
    uint8_t* op = g_o + (size_t)g * 147456 + half * 8192 + j * 1024 + wq * 256 + lane * 4;
    mbar_wait(kb0, 0);
    mbar_wait(kb0 + 16, 0);
    STAMP(2);
#pragma unroll
    for (int i = 0; i < 12; i++) o[i] = 0.f;
#pragma unroll
    for (int i = 0; i < 8; i++) pb[i] = 0u;
#pragma unroll 1
    for (int hh = 0;; hh++) {
      wg_wait<0>();
#pragma unroll
      for (int i = 0; i < 6; i++) asm volatile("xor.b32 %0, %1, %2;\n" : "=r"(q[i]) : "r"(qn[i]), "r"(vz));
      q[6] = q[4] & vz; q[7] = q[5] & vz;
      regfence(q); regfence(o); regfence(pb);
      wg_fence();
      wgmma_rs_n24_tb<H_NS, 0>(o, pb[0], pb[1], pb[2], pb[3], w);
      wgmma_rs_n24_tb<H_NS, 48>(o, pb[4], pb[5], pb[6], pb[7], w);
      wgmma_rs_n32_z<H_K, K0 + 192>(sa, q[0], q[1], q[2], q[3], wp);
      wgmma_rs_n32<H_K, K1 + 192>(sa, q[4], q[5], q[6], q[7], wp);
      wg_commit();
      wg_wait<0>();
      regfence(sa); regfence(o);
      if (hh > 0) {
        const int hp = hh - 1;
        uint32_t ob[6];
        auto normalise = [&](const float (&v)[12]) -> bool {
          const float l0 = __shfl_sync(0xffffffffu, hp < 3 ? v[8] : v[0], hp < 3 ? 3 : 0, 4);
          const float l1 = __shfl_sync(0xffffffffu, hp < 3 ? v[10] : v[2], hp < 3 ? 3 : 0, 4);
          float i0, i1;
          asm("rcp.approx.ftz.f32 %0, %1;\n" : "=f"(i0) : "f"(l0));
          asm("rcp.approx.ftz.f32 %0, %1;\n" : "=f"(i1) : "f"(l1));
#pragma unroll
          for (int i = 0; i < 6; i++) ob[i] = pack(v[2 * i] * ((i & 1) ? i1 : i0), v[2 * i + 1] * ((i & 1) ? i1 : i0));
          const uint32_t bad = hfma2(ob[0], vz, hfma2(ob[1], vz, hmul2(ob[2], vz))) | hfma2(ob[3], vz, hfma2(ob[4], vz, hmul2(ob[5], vz)));
          return (l0 >= 0x1p-103f) && (l0 <= 0x1p122f) && (l1 >= 0x1p-103f) && (l1 <= 0x1p122f) && ((bad & 0x7fff7fffu) == 0u);
        };
        if (__builtin_expect(__any_sync(0xffffffffu, !normalise(o)), 0)) {
          uint32_t qx[6]; float ox[12];
          const uint32_t tid = tid_now();
#pragma unroll
          for (int i = 0; i < 6; i++)
            qx[i] = (i < 2 ? c >= hp : i < 4 ? true : c <= hp) ? __ldcg(g_q + (size_t)(blockIdx.x * 2 + half) * 28 * 128 + (tid & 127) + (hp * 6 + i) * 128) : 0u;
          attn_exact(g_kv + (size_t)(j * 260 + 1) * 3072 + hp * KVH + 1536, qx, ox, tid & 31);
          normalise(ox);
        }
        asm volatile("{\n.reg .pred p, q;\nsetp.ge.s32 p, %7, %8;\nsetp.le.s32 q, %7, %8;\n"
                     "@p st.global.u32 [%0], %1;\n@p st.global.u32 [%0 + 128], %2;\nst.global.u32 [%0 + 16384], %3;\nst.global.u32 [%0 + 16512], %4;\n"
                     "@q st.global.u32 [%0 + 32768], %5;\n@q st.global.u32 [%0 + 32896], %6;\n}\n"
                     ::"l"(op), "r"(ob[0]), "r"(ob[1]), "r"(ob[2]), "r"(ob[3]), "r"(ob[4]), "r"(ob[5]), "r"(c), "r"(hp) : "memory");
        warp_arrive(bars + 8 * (SIG_O + hp));
        STAMP(3 + hp);
        if (hh == 4) break;
        op += 32768; qp += 768;
        static_for<6>([&](auto I) { constexpr int i = decltype(I)::value; qn[i] = ldcg_at<(6 + i) * 512>(qp); });
      }
#pragma unroll
      for (int i = 0; i < 12; i++) o[i] = 0.f;
#pragma unroll
      for (int i = 0; i < 8; i++) pb[i] = 0u;
      regfence(o); regfence(pb); regfence(sa);
#pragma unroll 1
      for (int hf = hh > 0; hf < 2; hf++) {
        att_loop<H_NS, H_K, K0, K1, SPIN_LIMIT>(o, sa, pb, q, w, wp, kb, kp, ph, dV, kb0, rdelta, two, P.zero, hh > 0 ? 32 : 16);
        if (hf == 0) {
          mbar_wait(bars + 8 * SIG_KV1, 0);
          static_for<6>([&](auto I) { constexpr int i = decltype(I)::value; qn[i] = ldcg_at<(6 + i) * 512>(qp); });
        }
      }
    }
    cluster_arrive();
    cluster_wait();
  } else {
    const int wq = __shfl_sync(0xffffffffu, ((int)threadIdx.x >> 5) & 3, 0);
    if (elect_one()) {
      auto init_range = [&](auto Q) {
        static_for<15>([&](auto I) {
          constexpr int i = decltype(Q)::value * 15 + decltype(I)::value;
          constexpr uint32_t cnt = i == SIG_O + ZLATE ? 9 : i == PA_DONE ? 8 : ((i >= B_EMPTY && i < A_FREE) || (i >= KV_BAR && i < DUMMY && ((i - KV_BAR) & 1))) ? 16 :
              (i < B_EMPTY || (i >= A_FULL && i < SIG_KV) || (i >= KV_BAR && i < DUMMY && ((i - KV_BAR) & 1) == 0) || i == DUMMY || i >= X_FULL) ? 1 : 8;
          mbar_init(bars + 8 * i, cnt);
        });
      };
      if (wq == 0) init_range(IC<0>{}); else if (wq == 1) init_range(IC<1>{}); else if (wq == 2) init_range(IC<2>{}); else init_range(IC<3>{});
      asm volatile("fence.mbarrier_init.release.cluster;\n" ::: "memory");
      fence_async_smem();
    }
    __syncwarp();
    cluster_arrive();
#pragma unroll
    for (int i = 0; i < 3; i++)
      if (wof[i] != 0xffffffffu) *reinterpret_cast<uint4*>(a_wq + j * 248832 + wof[i]) = wv[i];
    asm volatile("bar.arrive 1, 640;\n" ::: "memory");
    asm volatile("setmaxnreg.dec.sync.aligned.u32 24;\n");
    cluster_wait();
    PSTAMP(13);
    const unsigned int ep1 = *(volatile unsigned int*)(g_epoch + blockIdx.x) + 1;
    if (wq == 0) {
      PSTAMP(12);
      trap_if((sb & 1023) != 0);
      const int cm = j * 64, cr = 512 + j * 8;
      const uint64_t pol = (WPOL == 1 || (WPOL == 2 && g >= 14)) ? pol_stream() : pol_normal();
      uint32_t it = 0, dst = 0, fb = 0;
      auto acquire = [&]() {
        const uint32_t st = it & 3;
        mbar_wait(bars + 8 * (B_EMPTY + st), (it >> 2) & 1);
        dst = sb + OFF_B + st * 16384 + rank * 8192; fb = bars + 8 * (B_FULL + st);
        it++;
      };
      cnt_wait(cnt_wq, 16 * ep1);
      fence_async_global();
#pragma unroll 1
      for (int u = 0; u < 12; u++) {
        acquire();
        if (elect_one()) {
          mbar_expect(fb, 13824);
          bulk_load_mc(dst - rank * 1280, a_wq + j * 248832 + 82944 + u * 13824 + rank * 6912, 6912, fb, pol);
        }
      }
#pragma unroll 1
      for (int t = 0; t < 9; t++)
#pragma unroll 1
        for (int kb = 0; kb < 9; kb++) {
          acquire();
          if (elect_one()) {
            if (kb == 0) prefetch_tile(P, t + PFD, g, j);
            if (HPF && t == 7 && kb < 6) pf_bulk(g_h + (size_t)blockIdx.x * 147456 + kb * 16384, 16384);
            mbar_expect(fb, 16384);
            tma2d_mc(dst, &P.wg + rank, j * 576 + t * 64, kb * 64, fb, pol);
          }
        }
#pragma unroll 1
      for (int kb = 0; kb < 4; kb += 2) {
        acquire();
        if (elect_one()) {
          mbar_expect(fb, 16384);
          tma2d_mc(dst, &P.wd, ((j + 1) % 9) * 64, j * 576 + (kb + rank) * 64, fb, pol);
        }
      }
      {
        int kb = 4, col = (j + 1 + rank) % 9, T = 9 + PFD;
#pragma unroll 1
        for (int u = 0; u < 36; u++) {
          acquire();
          if (elect_one()) {
            if (kb == 4) prefetch_tile(P, T, g, j);
            mbar_expect(fb, 16384);
            tma2d_mc(dst, &P.wd, col * 64, j * 576 + kb * 64, fb, pol);
          }
          if (kb == 4) T++;
          if (++kb == 9) kb = 0;
          if (kb == rank * 4) col = col >= 7 ? col - 7 : col + 2;
        }
      }
#pragma unroll 1
      for (int kb = 4; kb < 9; kb += 2) {
        acquire();
        if (elect_one()) {
          mbar_expect(fb, kb < 8 ? 16384 : 8192);
          if (kb + rank < 9) tma2d_mc(dst, &P.wd, j * 64, j * 576 + (kb + rank) * 64, fb, pol);
        }
      }
#pragma unroll 1
      for (int t = 0; t < 9; t++) {
        acquire();
        if (elect_one()) {
          mbar_expect(fb, 8192 + 1024);
          tma3d_mc(dst, &P.wo + rank, rank ? cr : cm, t * 8, 0, fb);
        }
      }
    } else if (wq == 1) {
      cnt_wait2(cnt_xn, 8 * ep1, cnt_wq, 16 * ep1);
      fence_async_global();
      PSTAMP(14);
#pragma unroll 1
      for (int kb = 0; kb < 9; kb++)
        if (elect_one()) {
          if ((kb & 1) == 0) {
            const uint32_t fb = bars + 8 * (H0_FULL + (kb >> 1)), nb = kb < 8 ? 9216 : 4608;
            mbar_expect(fb, 2 * nb);
            bulk_load_mc(sb + OFF_B + kb * 9216 + rank * nb, a_wq + j * 248832 + kb * 9216 + rank * nb, nb, fb, pol_stream());
          }
          mbar_expect(bars + 8 * (X_FULL + kb), 16384);
          bulk_load_s(sb + OFF_A + kb * 16384, a_xn + g * 147456 + kb * 16384, 16384, bars + 8 * (X_FULL + kb), XPOL ? pol_stream() : pol_normal());
        }
      mbar_wait(bars + 8 * (ZLATE ? SIG_O : SIG_KV1), 0);
      __nanosleep(1000);
      float4* z = reinterpret_cast<float4*>(g_dacc + (size_t)(g * 8 * 72 + j * 9) * 128) + lane;
#pragma unroll 1
      for (int w = 0; w < 8; w++) {
#pragma unroll
        for (int i = 0; i < 9; i++) z[(w * 72 + i) * 32] = make_float4(0.f, 0.f, 0.f, 0.f);
        __nanosleep(400);
      }
      warp_arrive(bars + 8 * (SIG_O + ZLATE));
      mbar_wait(bars + 8 * (SIG_O + ZLATE), 0);
      cnt_wait(cnt_o, 8 * ep1);
      if (ZLATE) cnt_wait(cnt_o + 32, 8 * ep1);
#pragma unroll 1
      for (int kb = 0; kb < 8; kb++) {
        mbar_wait(bars + 8 * (A_FREE + kb), 0);
        if (kb == 0) { fence_gpu(); fence_async_global(); }
        if (elect_one()) mbar_expect(bars + 8 * (A_FULL + kb), 16384);
#pragma unroll 1
        for (int u = 0; u < HSPLIT; u++) {
          if (elect_one()) bulk_load_s(sb + OFF_A + kb * 16384 + u * (16384 / HSPLIT), g_h + (size_t)blockIdx.x * 147456 + kb * 16384 + u * (16384 / HSPLIT), 16384 / HSPLIT, bars + 8 * (A_FULL + kb), pol_stream());
          if (HSLEEP > 0 && u + 1 < HSPLIT) __nanosleep(HSLEEP);
        }
      }
#pragma unroll 1
      for (int t = 0; t < 9; t++) {
        if (t == 0) {
          mbar_wait(bars + 8 * (SIG_O + 2), 0);
          cnt_wait(cnt_o + 32, 8 * ep1); cnt_wait(cnt_o + 64, 8 * ep1); fence_async_global();
        }
        if (t == 6) { cnt_wait(cnt_o + 96, 8 * ep1); fence_async_global(); if (elect_one()) mbar_arrive(bars + 8 * O3_SEEN); }
        mbar_wait(bars + 8 * (A_FREE + t), t < 8 ? 1 : 0);
        if ((t & 1) == 0 && t < 8) PSTAMP(8 + (t >> 1));
        if (elect_one()) mbar_expect(bars + 8 * (A_FULL + t), 16384);
        const uint32_t piece = t < 6 ? 4096 : 16384;
#pragma unroll 1
        for (uint32_t u = 0; u < 16384; u += piece)
          if (elect_one()) bulk_load(sb + OFF_A + t * 16384 + u, g_o + (size_t)g * 147456 + t * 16384 + u, piece, bars + 8 * (A_FULL + t));
      }
    } else if (wq == 2) {
      if (lane < 9) asm volatile("prefetch.tensormap [%0];\n" ::"l"(&P.wg + lane) : "memory");
      __syncwarp();
      const uint8_t* src = g_kv + (size_t)j * 260 * 3072;
      const uint64_t pol = KPOL ? pol_stream() : pol_normal(), poln = H0POL ? pol_stream() : pol_normal();
      uint32_t st = 0, ph = 1, ready = 0;
      const int g2 = g & ~1;
#pragma unroll 1
      for (int s2 = 0; s2 < 34; s2++) {
        const uint32_t need = s2 < 32 ? 3u << ((g2 + (s2 >> 2) * 2) & 15) : 0u;
        if ((ready & need) != need) {
          uint32_t n = 0;
          do {
            unsigned int v;
            asm volatile("ld.relaxed.gpu.global.u32 %0, [%1];\n" : "=r"(v) : "l"(cnt_kv + (lane & 15)) : "memory");
            ready = __ballot_sync(0xffffffffu, v == ep1);
            trap_if(++n > SPIN_LIMIT);
          } while ((ready & need) != need);
          asm volatile("fence.acquire.gpu;\n" ::: "memory");
          fence_async_global();
          if (s2 == 0) PSTAMP(3);
        }
        if (s2 == 32) { cnt_wait(cnt_kv + 88 * 32, 16 * ep1); fence_async_global(); }
        const uint32_t fb = bars + 8 * KV_BAR + st * 16, dst = sb + OFF_KV + st * 6144;
        if (s2 >= 3) mbar_wait(fb + 8, ph);
        if (elect_one()) {
          mbar_expect(fb, 6144);
          const int n = 2 * s2 - 1 + rank;
          const int sv = n < 2 ? 0 : n < 66 ? ((4 * g2 + n - 2) & 63) + 2 : n, sk = n < 64 ? (4 * g2 + max(n, 0)) & 63 : n;
          bulk_load_mc(dst + rank * 3072, src + (1 + sv) * 3072, 1536, fb, poln);
          bulk_load_mc(dst + rank * 3072 + 1536, src + (1 + sk) * 3072 + 1536, 1536, fb, poln);
        }
        if (++st == 3) { st = 0; ph ^= 1; }
      }
      src += 34 * 6144;
#pragma unroll 1
      for (int w = 34; w < 130; w += 3) {
#pragma unroll
        for (int u = 0; u < 3; u++) {
          const uint32_t s3 = (u + 1) % 3, fb = bars + 8 * KV_BAR + s3 * 16;
          if (u == 2) ph ^= 1;
          mbar_wait(fb + 8, ph);
          if (elect_one()) {
            if (((w + u) & 15) == g && w + u + 24 < 130) pf_bulk(src + (u + 24) * 6144, 6144);
            mbar_expect(fb, 6144);
            bulk_load_mc(sb + OFF_KV + s3 * 6144 + rank * 3072, src + u * 6144 + rank * 3072, 3072, fb, pol);
          }
        }
        src += 3 * 6144;
      }
      mbar_wait(bars + 8 * (SIG_O + 3), 0);
      PSTAMP(6);
      if (elect_one()) {
        cnt_signal(cnt_o + 3 * 32);
        mbar_expect(bars + 8 * XS_FULL, 18432);
        tma2d(sb + OFF_KV, &P.xs, j * 64, g * 128, bars + 8 * XS_FULL);
        tma2d(sb + OFF_KV + 16384, &P.xs_rem, 512 + j * 8, g * 128, bars + 8 * XS_FULL);
      }
      PSTAMP(7);
    } else {
      mbar_wait(bars + 8 * X_FULL, 0);
      PSTAMP(0);
      if (lane < PFD) prefetch_tile(P, lane, g, j);
      __syncwarp();
      if (lane == 0) {
        mbar_wait(bars + 8 * SIG_KV, 0);
        PSTAMP(1);
        cnt_signal(cnt_kv + g);
        PSTAMP(2);
        mbar_wait(bars + 8 * SIG_KV1, 0);
        cnt_signal(cnt_kv + 88 * 32);
#pragma unroll 1
        for (int no = 0; no < 3; no++) {
          mbar_wait(bars + 8 * (SIG_O + no), 0);
          cnt_signal(cnt_o + no * 32);
        }
        mbar_wait(bars + 8 * SIG_RED, 0);
        PSTAMP(4);
        cnt_signal(cnt_red);
        PSTAMP(5);
      }
    }
    __syncwarp();
    cluster_arrive();
    cluster_wait();
    PDUMP();
  }
}

typedef CUresult (*EncodeFn)(CUtensorMap*, CUtensorMapDataType, cuuint32_t, void*, const cuuint64_t*, const cuuint64_t*, const cuuint32_t*,
                             const cuuint32_t*, CUtensorMapInterleave, CUtensorMapSwizzle, CUtensorMapL2promotion, CUtensorMapFloatOOBfill);

void encode(EncodeFn fn, CUtensorMap* tm, const void* base, int rank, cuuint64_t d0, cuuint64_t d1, cuuint64_t d2, cuuint64_t s1, cuuint64_t s2,
            cuuint32_t b0, cuuint32_t b1, cuuint32_t b2, CUtensorMapSwizzle sw) {
  cuuint64_t gd[3] = {d0, d1, d2};
  cuuint64_t gs[2] = {s1, s2};
  cuuint32_t bx[3] = {b0, b1, b2};
  cuuint32_t es[3] = {1, 1, 1};
  fn(tm, CU_TENSOR_MAP_DATA_TYPE_BFLOAT16, rank, const_cast<void*>(base), gd, gs, bx, es, CU_TENSOR_MAP_INTERLEAVE_NONE, sw,
     CU_TENSOR_MAP_L2_PROMOTION_L2_128B, CU_TENSOR_MAP_FLOAT_OOB_FILL_NONE);
}

}

extern "C" void kernel_launch(void* const* d_in, const int* in_sizes, int n_in, void* d_out, int out_size) {
  (void)in_sizes; (void)n_in; (void)out_size;
  static EncodeFn fn = nullptr;
  static uint8_t *s_xn, *s_wq;
  static unsigned int* s_cnt;
  if (!fn) {
    void* p = nullptr;
    cudaDriverEntryPointQueryResult qr;
    cudaGetDriverEntryPoint("cuTensorMapEncodeTiled", &p, cudaEnableDefault, &qr);
    fn = (EncodeFn)p;
    cudaGetSymbolAddress((void**)&s_xn, g_xn);
    cudaGetSymbolAddress((void**)&s_wq, g_wq);
    cudaGetSymbolAddress((void**)&s_cnt, g_cnt);
    cudaFuncSetAttribute(fused_kernel, cudaFuncAttributeMaxDynamicSharedMemorySize, SMEM_BYTES);
  }
  Params P;
  const CUtensorMapSwizzle SW = CU_TENSOR_MAP_SWIZZLE_128B;
  encode(fn, &P.xs, d_in[0], 2, 576, 2048, 1, 576 * 2, 0, 64, 128, 1, SW);
  encode(fn, &P.xs_rem, d_in[0], 2, 576, 2048, 1, 576 * 2, 0, 8, 128, 1, CU_TENSOR_MAP_SWIZZLE_NONE);
  encode(fn, &P.om, d_out, 2, 576, 2048, 1, 576 * 2, 0, 64, 64, 1, SW);
  encode(fn, &P.om_rem, d_out, 2, 576, 2048, 1, 576 * 2, 0, 8, 64, 1, CU_TENSOR_MAP_SWIZZLE_NONE);
  encode(fn, &P.wg, d_in[4], 2, 4608, 576, 1, 4608 * 2, 0, 64, 64, 1, SW);
  encode(fn, &P.wu, d_in[5], 2, 4608, 576, 1, 4608 * 2, 0, 64, 64, 1, SW);
  encode(fn, &P.wd, d_in[6], 2, 576, 4608, 1, 576 * 2, 0, 64, 64, 1, SW);
  encode(fn, &P.wo, d_in[2], 3, 576, 72, 8, 576 * 2, 72 * 576 * 2, 64, 8, 8, SW);
  encode(fn, &P.wo_rem, d_in[2], 3, 576, 72, 8, 576 * 2, 72 * 576 * 2, 8, 8, 8, SW);
  P.zero = 0;
  fused_kernel<<<NCTA, 640, SMEM_BYTES>>>((const uint32_t*)d_in[0], (const uint4*)d_in[1], s_xn, s_wq, s_cnt, P);
}
```
